```python
import torch

def _softmax(x, axis=-1):
    return torch.softmax(x, dim=axis)
def _gelu(x):
    return torch.nn.functional.gelu(x, approximate="tanh")
def _silu(x):
    return torch.nn.functional.silu(x)
def _sigmoid(x):
    return torch.sigmoid(x)
def _layernorm(x, axis=-1, eps=1e-5):
    m = x.mean(dim=axis, keepdim=True)
    v = x.var(dim=axis, keepdim=True, unbiased=False)
    return (x - m) / torch.sqrt(v + eps)
def _scatter_add(tgt, idx, src, axis=0):
    return tgt.clone().index_add_(axis, idx, src)
def _segment_sum(src, seg, n):
    out = torch.zeros((n,) + src.shape[1:], dtype=src.dtype)
    return out.index_add_(0, seg, src)
def _pad(x, pw):
    flat = tuple(v for pair in reversed(pw) for v in pair)
    return torch.nn.functional.pad(x, flat)

kernel_name = 'interleave_layers__gqa_block_cached__mixer_channel_mlp__decode'

def setup_inputs():

    _w = (lambda a: (lambda t: t.to(torch.bfloat16) if t.is_floating_point() else t)(torch.as_tensor(a)))
    def _A_setup():
        B, Sq, D = 1, 1, 640
        Hq, Hkv, Sk, Dh = 32, 32, 4096, 128
        assert Hq % Hkv == 0, (Hq, Hkv)
        return {
            "x": _w((lambda *s: torch.randn(*s, dtype=torch.bfloat16) * 0.05)(B, Sq, D)),
            "k_cache": _w((lambda *s: torch.randn(*s, dtype=torch.bfloat16) * 3.2)(B, Hkv, Sk, Dh)),
            "v_cache": _w((lambda *s: torch.randn(*s, dtype=torch.bfloat16) * 0.4)(B, Hkv, Sk, Dh)),
            "wq": _w((lambda *s: torch.randn(*s, dtype=torch.bfloat16) * 3.2)(D, Hq * Dh) * (D ** -0.5)),
            "wo": _w((lambda *s: torch.randn(*s, dtype=torch.bfloat16) * 0.4)(Hq * Dh, D) * ((Hq * Dh) ** -0.5)),
        }
    _A_in = _A_setup()

    def _B_setup():
        B, S, D, F = 1, 1, 640, 1728
        return {
            "x": _w((lambda *s: torch.randn(*s, dtype=torch.bfloat16) * 0.05)(B, S, D)),
            "w1": _w((lambda *s: torch.randn(*s, dtype=torch.bfloat16) * 0.4)(D, F) * (D ** -0.5)),
            "b1": _w((lambda *s: torch.randn(*s, dtype=torch.bfloat16) * 0.4)(F)),
            "w2": _w((lambda *s: torch.randn(*s, dtype=torch.bfloat16) * 0.4)(F, D) * (F ** -0.5)),
            "b2": _w((lambda *s: torch.randn(*s, dtype=torch.bfloat16) * 0.2)(D)),
        }
    _B_in = _B_setup()

    return {
        "A_x": _A_in["x"],
        "A_k_cache": _A_in["k_cache"],
        "A_v_cache": _A_in["v_cache"],
        "A_wq": _A_in["wq"],
        "A_wo": _A_in["wo"],
        "B_x": _B_in["x"],
        "B_w1": _B_in["w1"],
        "B_b1": _B_in["b1"],
        "B_w2": _B_in["w2"],
        "B_b2": _B_in["b2"],
    }

def reference(A_x, A_k_cache, A_v_cache, A_wq, A_wo, B_x, B_w1, B_b1, B_w2, B_b2):
    def _A_ref(x, k_cache, v_cache, wq, wo):
        B, Sq, D = x.shape
        Hq, Dh = 32, 128
        Hkv = k_cache.shape[1]
        rep = Hq // Hkv
        q = (lambda x, *d: x.permute(*d))((x @ wq).reshape(B, Sq, Hq, Dh), 0, 2, 1, 3)
        k = (lambda x, n, axis: torch.repeat_interleave(x, n, dim=axis))(k_cache, rep, axis=1)
        v = (lambda x, n, axis: torch.repeat_interleave(x, n, dim=axis))(v_cache, rep, axis=1)
        scores = torch.einsum("bhqd,bhkd->bhqk", q, k) * (Dh ** -0.5)
        p = _softmax(scores, axis=-1)
        o = torch.einsum("bhqk,bhkd->bhqd", p, v)
        return (lambda x, *d: x.permute(*d))(o, 0, 2, 1, 3).reshape(B, Sq, Hq * Dh) @ wo

    def _B_ref(x, w1, b1, w2, b2):
        y = _layernorm(x, axis=-1)
        h = _gelu(torch.einsum("bsd,df->bsf", y, w1) + b1)
        return torch.einsum("bsf,fd->bsd", h, w2) + b2

    x = A_x
    x = x + _A_ref(_layernorm(x, axis=-1), A_k_cache, A_v_cache, A_wq, A_wo)
    x = x + _B_ref(_layernorm(x, axis=-1), B_w1, B_b1, B_w2, B_b2)
    x = x + _A_ref(_layernorm(x, axis=-1), A_k_cache, A_v_cache, A_wq, A_wo)
    x = x + _B_ref(_layernorm(x, axis=-1), B_w1, B_b1, B_w2, B_b2)
    return x
```

```cpp
#include <cuda_runtime.h>
#include <cuda_bf16.h>
#include <cuda.h>
#include <stdint.h>

namespace {

constexpr int D_MODEL = 640;
constexpr int NHEAD = 32;
constexpr int SK = 4096;
constexpr int DH = 128;
constexpr int FF = 1728;
constexpr int NCTA = 128;
constexpr int TILE_KEYS = 64;
constexpr int TILE_BYTES = TILE_KEYS * DH * 2;
constexpr int NT = 16;
constexpr int NSLOT = 13;
constexpr int RETAIN = 10;
constexpr int NCOMP = 256;
constexpr int NTHREADS = NCOMP + 32;
constexpr int MLP_CTAS = FF / 16;
constexpr int SPIN_LIMIT = 1 << 22;

constexpr int SM_SLOTS = 0;
constexpr int SM_A = NSLOT * TILE_BYTES;
constexpr int SM_B = SM_A + 8192;
constexpr int SM_P = SM_B + 4096;
constexpr int SM_XN = SM_P + 2048;
constexpr int SM_MISC = SM_XN + 2560;
constexpr int SM_BAR = SM_MISC + 1024;
constexpr int SM_TAB = SM_BAR + 256;
constexpr int SM_TOTAL = SM_TAB + 64;

struct Scratch {
    unsigned epoch;
    unsigned pad0[31];
    unsigned cnt[4 * 32];
    float acc[2][4][D_MODEL];
    unsigned long long qx[2][NCTA][DH];
    unsigned long long ox[2][NCTA][DH + 8];
};
__device__ Scratch g_s;
#define FAIL(code) __trap()
#define ABORTED() false

__device__ __forceinline__ float bf16r(float x) { return __bfloat162float(__float2bfloat16_rn(x)); }
__device__ __forceinline__ float bf_lo(unsigned u) { return __uint_as_float(u << 16); }
__device__ __forceinline__ float bf_hi(unsigned u) { return __uint_as_float(u & 0xffff0000u); }
__device__ __forceinline__ uint32_t smem_u32(const void* p) { return (uint32_t)__cvta_generic_to_shared(p); }

__device__ __forceinline__ void bar_comp() { asm volatile("bar.sync 1, 256;" ::: "memory"); }

__device__ __forceinline__ void mbar_init(uint32_t bar, int count) {
    asm volatile("mbarrier.init.shared::cta.b64 [%0], %1;" ::"r"(bar), "r"(count) : "memory");
}
__device__ __forceinline__ void mbar_arrive(uint32_t bar) {
    asm volatile("mbarrier.arrive.shared::cta.b64 _, [%0];" ::"r"(bar) : "memory");
}
__device__ __forceinline__ void mbar_expect_tx(uint32_t bar, int bytes) {
    asm volatile("mbarrier.arrive.expect_tx.shared::cta.b64 _, [%0], %1;" ::"r"(bar), "r"(bytes) : "memory");
}
__device__ __forceinline__ void mbar_wait(uint32_t bar, uint32_t parity, int code = 1) {
    uint32_t done = 0;
    for (int it = 0; it < SPIN_LIMIT; ++it) {
        if (ABORTED()) return;
        asm volatile(
            "{\n.reg .pred p;\n"
            "mbarrier.try_wait.parity.shared::cta.b64 p, [%1], %2;\n"
            "selp.u32 %0, 1, 0, p;\n}\n"
            : "=r"(done) : "r"(bar), "r"(parity) : "memory");
        if (done) return;
    }
    FAIL(code);
}
__device__ __forceinline__ void tma_load_2d(uint32_t dst, const CUtensorMap* tm, int c0, int c1, uint32_t bar,
                                            unsigned long long policy) {
    asm volatile(
        "cp.async.bulk.tensor.2d.shared::cluster.global.mbarrier::complete_tx::bytes.L2::cache_hint "
        "[%0], [%1, {%3, %4}], [%2], %5;"
        ::"r"(dst), "l"((unsigned long long)tm), "r"(bar), "r"(c0), "r"(c1), "l"(policy) : "memory");
}
__device__ __forceinline__ void ldsm_x4(uint32_t addr, uint32_t* r) {
    asm volatile("ldmatrix.sync.aligned.m8n8.x4.shared.b16 {%0,%1,%2,%3}, [%4];"
                 : "=r"(r[0]), "=r"(r[1]), "=r"(r[2]), "=r"(r[3]) : "r"(addr) : "memory");
}
__device__ __forceinline__ void ldsm_x4_t(uint32_t addr, uint32_t* r) {
    asm volatile("ldmatrix.sync.aligned.m8n8.x4.trans.shared.b16 {%0,%1,%2,%3}, [%4];"
                 : "=r"(r[0]), "=r"(r[1]), "=r"(r[2]), "=r"(r[3]) : "r"(addr) : "memory");
}
__device__ __forceinline__ void mma_bf16(float* c, const uint32_t* a, uint32_t b0, uint32_t b1) {
    asm volatile(
        "mma.sync.aligned.m16n8k16.row.col.f32.bf16.bf16.f32 {%0,%1,%2,%3}, {%4,%5,%6,%7}, {%8,%9}, {%0,%1,%2,%3};"
        : "+f"(c[0]), "+f"(c[1]), "+f"(c[2]), "+f"(c[3])
        : "r"(a[0]), "r"(a[1]), "r"(a[2]), "r"(a[3]), "r"(b0), "r"(b1));
}
__device__ __forceinline__ void ll_store(unsigned long long* p, float v, unsigned tag) {
    unsigned long long w = ((unsigned long long)tag << 32) | (unsigned long long)__float_as_uint(v);
    asm volatile("st.relaxed.gpu.global.u64 [%0], %1;" ::"l"(p), "l"(w) : "memory");
}
__device__ __forceinline__ float ll_wait(const unsigned long long* p, unsigned tag, int code = 2) {
    unsigned long long w;
    for (int it = 0; it < SPIN_LIMIT; ++it) {
        if (ABORTED()) return 0.f;
        asm volatile("ld.relaxed.gpu.global.u64 %0, [%1];" : "=l"(w) : "l"(p) : "memory");
        if ((unsigned)(w >> 32) == tag) return __uint_as_float((unsigned)w);
    }
    FAIL(code);
    return 0.f;
}
__device__ __forceinline__ uint4 ldg_nc(const void* p) {
    uint4 v;
    asm volatile("ld.global.nc.L1::no_allocate.v4.u32 {%0,%1,%2,%3}, [%4];"
                 : "=r"(v.x), "=r"(v.y), "=r"(v.z), "=r"(v.w) : "l"(p));
    return v;
}
__device__ __forceinline__ float4 ldg_cg4(const float* p) {
    float4 v;
    asm volatile("ld.relaxed.gpu.global.v4.f32 {%0,%1,%2,%3}, [%4];"
                 : "=f"(v.x), "=f"(v.y), "=f"(v.z), "=f"(v.w) : "l"(p) : "memory");
    return v;
}
__device__ __forceinline__ void red_add4(float* p, float4 v) {
    asm volatile("red.relaxed.gpu.global.add.v4.f32 [%0], {%1,%2,%3,%4};"
                 ::"l"(p), "f"(v.x), "f"(v.y), "f"(v.z), "f"(v.w) : "memory");
}
__device__ __forceinline__ void fma8(float* acc, float s, const uint4& w) {
    acc[0] = fmaf(s, bf_lo(w.x), acc[0]); acc[1] = fmaf(s, bf_hi(w.x), acc[1]);
    acc[2] = fmaf(s, bf_lo(w.y), acc[2]); acc[3] = fmaf(s, bf_hi(w.y), acc[3]);
    acc[4] = fmaf(s, bf_lo(w.z), acc[4]); acc[5] = fmaf(s, bf_hi(w.z), acc[5]);
    acc[6] = fmaf(s, bf_lo(w.w), acc[6]); acc[7] = fmaf(s, bf_hi(w.w), acc[7]);
}
__device__ __forceinline__ float warp_sum(float v) {
#pragma unroll
    for (int o = 16; o > 0; o >>= 1) v += __shfl_xor_sync(0xffffffffu, v, o);
    return v;
}
__device__ __forceinline__ float warp_max(float v) {
#pragma unroll
    for (int o = 16; o > 0; o >>= 1) v = fmaxf(v, __shfl_xor_sync(0xffffffffu, v, o));
    return v;
}
__device__ __forceinline__ void layernorm_warp(const float* x, float* y) {
    float s = 0.f;
#pragma unroll
    for (int i = 0; i < 20; ++i) s += x[i];
    s = warp_sum(s);
    const float mean = s * (1.0f / D_MODEL);
    float v = 0.f;
#pragma unroll
    for (int i = 0; i < 20; ++i) { float d = x[i] - mean; v = fmaf(d, d, v); }
    v = warp_sum(v);
    const float mb = bf16r(mean);
    const float vb = bf16r(v * (1.0f / D_MODEL));
    const float den = bf16r(sqrtf(bf16r(vb + 1e-5f)));
#pragma unroll
    for (int i = 0; i < 20; ++i) y[i] = bf16r(__fdiv_rn(bf16r(x[i] - mb), den));
}

__device__ __forceinline__ void grid_arrive(int ph) {
    __threadfence();
    asm volatile("red.release.gpu.global.add.u32 [%0], 1;" ::"l"(&g_s.cnt[ph * 32]) : "memory");
}
__device__ __forceinline__ void grid_wait(int ph, unsigned target) {
    unsigned v;
    for (int it = 0; it < SPIN_LIMIT; ++it) {
        if (ABORTED()) return;
        asm volatile("ld.acquire.gpu.global.u32 %0, [%1];" : "=r"(v) : "l"(&g_s.cnt[ph * 32]) : "memory");
        if ((int)(v - target) >= 0) return;
    }
    FAIL(3 + ph);
}

__global__ void __launch_bounds__(NTHREADS, 1)
fused_kernel(const __grid_constant__ CUtensorMap tmK, const __grid_constant__ CUtensorMap tmV,
             const __nv_bfloat16* __restrict__ x_in, const __nv_bfloat16* __restrict__ wq,
             const __nv_bfloat16* __restrict__ wo, const __nv_bfloat16* __restrict__ w1,
             const __nv_bfloat16* __restrict__ b1, const __nv_bfloat16* __restrict__ w2,
             const __nv_bfloat16* __restrict__ b2, __nv_bfloat16* __restrict__ out) {
    extern __shared__ __align__(1024) unsigned char smem[];
    const int tid = threadIdx.x;
    const int warp = tid >> 5;
    const int lane = tid & 31;
    const int cta = blockIdx.x;
    const int head = cta >> 2;
    const int quarter = cta & 3;
    const uint32_t sbase = smem_u32(smem);
    const uint32_t bar_full = sbase + SM_BAR;
    const uint32_t bar_empty = sbase + SM_BAR + NSLOT * 8;
    unsigned char* slot_tab = smem + SM_TAB;

    if (tid == 0) {
        for (int s = 0; s < NSLOT; ++s) { mbar_init(bar_full + s * 8, 1); mbar_init(bar_empty + s * 8, 8); }
        for (int n = 0; n < 32; ++n) slot_tab[n] = (n < RETAIN) ? n : RETAIN + (n - RETAIN) % (NSLOT - RETAIN);
        for (int c = 0; c < 32; ++c) {
            int s;
            if (c < RETAIN) s = c;
            else {
                int j = c - RETAIN;
                s = (j < NSLOT - RETAIN) ? RETAIN + j : slot_tab[32 + j - (NSLOT - RETAIN)];
            }
            slot_tab[32 + c] = s;
        }
        asm volatile("fence.mbarrier_init.release.cluster;" ::: "memory");
    }
    __syncthreads();

    if (warp == 8) {
        if (lane == 0) {
            unsigned long long pol_first, pol_norm;
            asm volatile("createpolicy.fractional.L2::evict_first.b64 %0, 1.0;" : "=l"(pol_first));
            asm volatile("createpolicy.fractional.L2::evict_normal.b64 %0, 1.0;" : "=l"(pol_norm));
            const int row0 = head * SK + quarter * 1024;
            uint32_t used = 0, epar = 0;
            for (int n = 0; n < 64; ++n) {
                const int pass = n >> 5, t = n & 31;
                if (pass == 1 && t < RETAIN) continue;
                const int s = slot_tab[n];
                if (used & (1u << s)) { mbar_wait(bar_empty + s * 8, (epar >> s) & 1, 10 + n); epar ^= (1u << s); }
                used |= (1u << s);
                const CUtensorMap* tm = (t < 16) ? &tmK : &tmV;
                const int row = row0 + (t & 15) * TILE_KEYS;
                const unsigned long long pol = (pass == 1 || t < RETAIN) ? pol_first : pol_norm;
                const uint32_t dst = sbase + SM_SLOTS + s * TILE_BYTES;
                mbar_expect_tx(bar_full + s * 8, TILE_BYTES);
                tma_load_2d(dst, tm, 0, row, bar_full + s * 8, pol);
                tma_load_2d(dst + TILE_BYTES / 2, tm, 64, row, bar_full + s * 8, pol);
            }
        }
        return;
    }

    float* scores = reinterpret_cast<float*>(smem + SM_A);
    __nv_bfloat16* pbf = reinterpret_cast<__nv_bfloat16*>(smem + SM_P);
    float* gscr = reinterpret_cast<float*>(smem + SM_A);
    float* redb = reinterpret_cast<float*>(smem + SM_B);
    float* xn_s = reinterpret_cast<float*>(smem + SM_XN);
    float* misc = reinterpret_cast<float*>(smem + SM_MISC);
    const int g = lane >> 2, t4 = lane & 3;

    unsigned epoch;
    asm volatile("ld.relaxed.gpu.global.u32 %0, [%1];" : "=r"(epoch) : "l"(&g_s.epoch) : "memory");
    const int par = epoch & 1;
    if (cta == 1) {
        float* z = &g_s.acc[par ^ 1][0][0];
        for (int i = tid; i < 4 * D_MODEL; i += NCOMP) z[i] = 0.f;
    }
    {
        const char* p = reinterpret_cast<const char*>(wo + (size_t)(head * DH + quarter * 32) * D_MODEL);
        for (int i = tid; i < 32 * D_MODEL * 2 / 128; i += NCOMP)
            asm volatile("prefetch.global.L2 [%0];" ::"l"(p + (size_t)i * 128));
        if (cta < MLP_CTAS) {
            for (int i = tid; i < D_MODEL; i += NCOMP)
                asm volatile("prefetch.global.L2 [%0];" ::"l"(w1 + (size_t)i * FF + cta * 16));
            const char* p2 = reinterpret_cast<const char*>(w2 + (size_t)(cta * 16) * D_MODEL);
            for (int i = tid; i < 16 * D_MODEL * 2 / 128; i += NCOMP)
                asm volatile("prefetch.global.L2 [%0];" ::"l"(p2 + (size_t)i * 128));
        }
    }

    float xr[20];
#pragma unroll
    for (int j = 0; j < 5; ++j) {
        uint2 u = *reinterpret_cast<const uint2*>(x_in + lane * 4 + 128 * j);
        xr[j * 4 + 0] = bf_lo(u.x); xr[j * 4 + 1] = bf_hi(u.x);
        xr[j * 4 + 2] = bf_lo(u.y); xr[j * 4 + 3] = bf_hi(u.y);
    }

    uint32_t fpar = 0;

    for (int layer = 0; layer < 2; ++layer) {
        const unsigned tag = epoch * 2 + layer + 1;
        uint4 wv[11];
        {
            const __nv_bfloat16* wp = wq + (size_t)(quarter * 160 + (tid >> 4)) * (NHEAD * DH) + head * DH + (tid & 15) * 8;
#pragma unroll
            for (int i = 0; i < 10; ++i) wv[i] = ldg_nc(wp + (size_t)(16 * i) * (NHEAD * DH));
        }
        {
            float y[20];
            layernorm_warp(xr, y);
#pragma unroll
            for (int j = 0; j < 5; ++j) {
                const int e = lane * 4 + 128 * j;
                if (e / 80 == warp) *reinterpret_cast<float4*>(xn_s + e) = make_float4(y[j * 4], y[j * 4 + 1], y[j * 4 + 2], y[j * 4 + 3]);
            }
        }
        bar_comp();
        {
            float acc[8];
#pragma unroll
            for (int i = 0; i < 8; ++i) acc[i] = 0.f;
#pragma unroll
            for (int i = 0; i < 10; ++i) fma8(acc, xn_s[quarter * 160 + (tid >> 4) + 16 * i], wv[i]);
#pragma unroll
            for (int i = 0; i < 8; ++i) acc[i] += __shfl_xor_sync(0xffffffffu, acc[i], 16);
            if (lane < 16) {
                *reinterpret_cast<float4*>(redb + warp * 128 + lane * 8) = make_float4(acc[0], acc[1], acc[2], acc[3]);
                *reinterpret_cast<float4*>(redb + warp * 128 + lane * 8 + 4) = make_float4(acc[4], acc[5], acc[6], acc[7]);
            }
        }
        bar_comp();
        if (tid < 128) {
            float s = 0.f;
#pragma unroll
            for (int w = 0; w < 8; ++w) s += redb[w * 128 + tid];
            ll_store(&g_s.qx[layer][cta][tid], s, tag);
            float q = 0.f;
#pragma unroll
            for (int p = 0; p < 4; ++p) q += ll_wait(&g_s.qx[layer][head * 4 + p][tid], tag);
            reinterpret_cast<__nv_bfloat16*>(misc + 64)[tid] = __float2bfloat16_rn(q);
        }
        bar_comp();
        const int half = warp >> 2, grp = warp & 3;
        uint32_t qb[8];
        {
            const uint32_t* qw = reinterpret_cast<const uint32_t*>(misc + 64) + half * 32;
#pragma unroll
            for (int kk = 0; kk < 4; ++kk) {
                qb[kk * 2] = (g == 0) ? qw[kk * 8 + t4] : 0u;
                qb[kk * 2 + 1] = (g == 0) ? qw[kk * 8 + 4 + t4] : 0u;
            }
        }
        for (int c = 0; c < 16; ++c) {
            const int s = slot_tab[layer * 32 + c];
            if (!(layer == 1 && c < RETAIN)) {
                mbar_wait(bar_full + s * 8, (fpar >> s) & 1, 80 + layer * 32 + c);
                fpar ^= (1u << s);
            }
            const uint32_t tb = sbase + SM_SLOTS + s * TILE_BYTES + half * 8192;
            const int row = grp * 16 + (lane & 7) + ((lane >> 3) & 1) * 8;
            float cacc[4] = {0.f, 0.f, 0.f, 0.f};
#pragma unroll
            for (int kk = 0; kk < 4; ++kk) {
                uint32_t a[4];
                const int chunk = kk * 2 + (lane >> 4);
                ldsm_x4(tb + row * 128 + ((chunk ^ (row & 7)) << 4), a);
                mma_bf16(cacc, a, qb[kk * 2], qb[kk * 2 + 1]);
            }
            __syncwarp();
            if (lane == 0 && !(layer == 0 && c < RETAIN)) mbar_arrive(bar_empty + s * 8);
            if (t4 == 0) {
                scores[half * 1024 + c * 64 + grp * 16 + g] = cacc[0];
                scores[half * 1024 + c * 64 + grp * 16 + g + 8] = cacc[2];
            }
        }
        bar_comp();
        float sc[4];
        {
            const float4 s0 = *reinterpret_cast<const float4*>(scores + tid * 4);
            const float4 s1 = *reinterpret_cast<const float4*>(scores + 1024 + tid * 4);
            sc[0] = bf16r(bf16r(s0.x + s1.x) * 0.08838834764831845f);
            sc[1] = bf16r(bf16r(s0.y + s1.y) * 0.08838834764831845f);
            sc[2] = bf16r(bf16r(s0.z + s1.z) * 0.08838834764831845f);
            sc[3] = bf16r(bf16r(s0.w + s1.w) * 0.08838834764831845f);
            const float wmax = warp_max(fmaxf(fmaxf(sc[0], sc[1]), fmaxf(sc[2], sc[3])));
            if (lane == 0) misc[warp] = wmax;
        }
        bar_comp();
        float mloc = misc[0];
#pragma unroll
        for (int w = 1; w < 8; ++w) mloc = fmaxf(mloc, misc[w]);
        {
            const float e0 = __expf(sc[0] - mloc), e1 = __expf(sc[1] - mloc), e2 = __expf(sc[2] - mloc), e3 = __expf(sc[3] - mloc);
            __nv_bfloat162 p01 = __floats2bfloat162_rn(e0, e1), p23 = __floats2bfloat162_rn(e2, e3);
            uint2 pk;
            pk.x = *reinterpret_cast<uint32_t*>(&p01); pk.y = *reinterpret_cast<uint32_t*>(&p23);
            *reinterpret_cast<uint2*>(pbf + tid * 4) = pk;
            float ls = warp_sum((e0 + e1) + (e2 + e3));
            if (lane == 0) misc[8 + warp] = ls;
        }
        bar_comp();
        float lloc = 0.f;
#pragma unroll
        for (int w = 0; w < 8; ++w) lloc += misc[8 + w];
        float oacc[4][4];
#pragma unroll
        for (int dd = 0; dd < 4; ++dd) { oacc[dd][0] = oacc[dd][1] = oacc[dd][2] = oacc[dd][3] = 0.f; }
        for (int c = 0; c < 16; ++c) {
            const int s = slot_tab[layer * 32 + 16 + c];
            mbar_wait(bar_full + s * 8, (fpar >> s) & 1, 96 + layer * 32 + c);
            fpar ^= (1u << s);
            const uint32_t tb = sbase + SM_SLOTS + s * TILE_BYTES + half * 8192;
            const uint32_t* pw = reinterpret_cast<const uint32_t*>(pbf + c * 64 + grp * 16);
            const uint32_t b0 = (g == 0) ? pw[t4] : 0u;
            const uint32_t b1 = (g == 0) ? pw[4 + t4] : 0u;
            const int key = grp * 16 + (lane & 7) + (lane >> 4) * 8;
#pragma unroll
            for (int dd = 0; dd < 4; ++dd) {
                uint32_t a[4];
                const int chunk = dd * 2 + ((lane >> 3) & 1);
                ldsm_x4_t(tb + key * 128 + ((chunk ^ (key & 7)) << 4), a);
                mma_bf16(oacc[dd], a, b0, b1);
            }
            __syncwarp();
            if (lane == 0) mbar_arrive(bar_empty + s * 8);
        }
        {
            const int chunk = tid % 80, rg = tid / 80;
            const __nv_bfloat16* wp = wo + (size_t)(head * DH + quarter * 32 + rg) * D_MODEL + chunk * 8;
#pragma unroll
            for (int i = 0; i < 11; ++i)
                if (tid < 240 && rg + 3 * i < 32) wv[i] = ldg_nc(wp + (size_t)(3 * i) * D_MODEL);
        }
        if (t4 == 0) {
#pragma unroll
            for (int dd = 0; dd < 4; ++dd) {
                redb[grp * 128 + half * 64 + dd * 16 + g] = oacc[dd][0];
                redb[grp * 128 + half * 64 + dd * 16 + g + 8] = oacc[dd][2];
            }
        }
        bar_comp();
        if (tid < 128) {
            float s = (redb[tid] + redb[128 + tid]) + (redb[256 + tid] + redb[384 + tid]);
            ll_store(&g_s.ox[layer][cta][tid], s, tag);
            if (tid == 0) ll_store(&g_s.ox[layer][cta][128], mloc, tag);
            if (tid == 1) ll_store(&g_s.ox[layer][cta][129], lloc, tag);
            const int p = warp;
            const unsigned long long* src = &g_s.ox[layer][head * 4 + p][0];
            float mm[4];
#pragma unroll
            for (int pp = 0; pp < 4; ++pp) mm[pp] = ll_wait(&g_s.ox[layer][head * 4 + pp][128], tag);
            const float lp = ll_wait(src + 129, tag);
            const float op = ll_wait(src + quarter * 32 + lane, tag);
            const float M = fmaxf(fmaxf(mm[0], mm[1]), fmaxf(mm[2], mm[3]));
            const float wgt = __expf(mm[p] - M);
            misc[128 + p * 32 + lane] = op * wgt;
            if (lane == 0) misc[16 + p] = lp * wgt;
        }
        bar_comp();
        if (tid < 32) {
            const float L = (misc[16] + misc[17]) + (misc[18] + misc[19]);
            const float o = (misc[128 + tid] + misc[160 + tid]) + (misc[192 + tid] + misc[224 + tid]);
            misc[32 + tid] = bf16r(__fdiv_rn(o, L));
        }
        bar_comp();
        if (tid < 240) {
            const int chunk = tid % 80, rg = tid / 80;
            float acc[8];
#pragma unroll
            for (int i = 0; i < 8; ++i) acc[i] = 0.f;
#pragma unroll
            for (int i = 0; i < 11; ++i)
                if (rg + 3 * i < 32) fma8(acc, misc[32 + rg + 3 * i], wv[i]);
            *reinterpret_cast<float4*>(gscr + rg * 640 + chunk * 8) = make_float4(acc[0], acc[1], acc[2], acc[3]);
            *reinterpret_cast<float4*>(gscr + rg * 640 + chunk * 8 + 4) = make_float4(acc[4], acc[5], acc[6], acc[7]);
        }
        bar_comp();
        if (tid < 160) {
            float4 a = *reinterpret_cast<const float4*>(gscr + tid * 4);
            float4 b = *reinterpret_cast<const float4*>(gscr + 640 + tid * 4);
            float4 c = *reinterpret_cast<const float4*>(gscr + 1280 + tid * 4);
            red_add4(&g_s.acc[par][layer * 2][tid * 4], make_float4(a.x + b.x + c.x, a.y + b.y + c.y, a.z + b.z + c.z, a.w + b.w + c.w));
        }
        bar_comp();
        if (tid == 0) grid_arrive(layer * 2);
        uint4 w2v[6];
        if (cta < MLP_CTAS) {
            const __nv_bfloat16* wp = w1 + (size_t)(tid >> 1) * FF + cta * 16 + (tid & 1) * 8;
#pragma unroll
            for (int i = 0; i < 5; ++i) wv[i] = ldg_nc(wp + (size_t)(128 * i) * FF);
            const int chunk = tid % 80, rg = tid / 80;
            const __nv_bfloat16* wp2 = w2 + (size_t)(cta * 16 + rg) * D_MODEL + chunk * 8;
#pragma unroll
            for (int i = 0; i < 6; ++i)
                if (tid < 240 && rg + 3 * i < 16) w2v[i] = ldg_nc(wp2 + (size_t)(3 * i) * D_MODEL);
        }
        if (tid == 0) grid_wait(layer * 2, (epoch + 1) * NCTA);
        bar_comp();
#pragma unroll
        for (int j = 0; j < 5; ++j) {
            float4 a = ldg_cg4(&g_s.acc[par][layer * 2][lane * 4 + 128 * j]);
            xr[j * 4 + 0] = bf16r(xr[j * 4 + 0] + bf16r(a.x));
            xr[j * 4 + 1] = bf16r(xr[j * 4 + 1] + bf16r(a.y));
            xr[j * 4 + 2] = bf16r(xr[j * 4 + 2] + bf16r(a.z));
            xr[j * 4 + 3] = bf16r(xr[j * 4 + 3] + bf16r(a.w));
        }
        if (cta < MLP_CTAS) {
            {
                float y[20], y2[20];
                layernorm_warp(xr, y);
                layernorm_warp(y, y2);
#pragma unroll
                for (int j = 0; j < 5; ++j) {
                    const int e = lane * 4 + 128 * j;
                    if (e / 80 == warp) *reinterpret_cast<float4*>(xn_s + e) = make_float4(y2[j * 4], y2[j * 4 + 1], y2[j * 4 + 2], y2[j * 4 + 3]);
                }
            }
            bar_comp();
            {
                float acc[8];
#pragma unroll
                for (int i = 0; i < 8; ++i) acc[i] = 0.f;
#pragma unroll
                for (int i = 0; i < 5; ++i) fma8(acc, xn_s[(tid >> 1) + 128 * i], wv[i]);
#pragma unroll
                for (int o = 2; o <= 16; o <<= 1)
#pragma unroll
                    for (int i = 0; i < 8; ++i) acc[i] += __shfl_xor_sync(0xffffffffu, acc[i], o);
                if (lane < 2) {
                    *reinterpret_cast<float4*>(redb + warp * 16 + lane * 8) = make_float4(acc[0], acc[1], acc[2], acc[3]);
                    *reinterpret_cast<float4*>(redb + warp * 16 + lane * 8 + 4) = make_float4(acc[4], acc[5], acc[6], acc[7]);
                }
            }
            bar_comp();
            if (tid < 16) {
                float s = 0.f;
#pragma unroll
                for (int w = 0; w < 8; ++w) s += redb[w * 16 + tid];
                const float u = bf16r(bf16r(s) + __bfloat162float(b1[cta * 16 + tid]));
                const float inner = 0.7978845608028654f * (u + 0.044715f * u * u * u);
                misc[16 + tid] = bf16r(0.5f * u * (1.0f + tanhf(inner)));
            }
            bar_comp();
            if (tid < 240) {
                const int chunk = tid % 80, rg = tid / 80;
                float acc[8];
#pragma unroll
                for (int i = 0; i < 8; ++i) acc[i] = 0.f;
#pragma unroll
                for (int i = 0; i < 6; ++i)
                    if (rg + 3 * i < 16) fma8(acc, misc[16 + rg + 3 * i], w2v[i]);
                *reinterpret_cast<float4*>(gscr + rg * 640 + chunk * 8) = make_float4(acc[0], acc[1], acc[2], acc[3]);
                *reinterpret_cast<float4*>(gscr + rg * 640 + chunk * 8 + 4) = make_float4(acc[4], acc[5], acc[6], acc[7]);
            }
            bar_comp();
            if (tid < 160) {
                float4 a = *reinterpret_cast<const float4*>(gscr + tid * 4);
                float4 b = *reinterpret_cast<const float4*>(gscr + 640 + tid * 4);
                float4 c = *reinterpret_cast<const float4*>(gscr + 1280 + tid * 4);
                red_add4(&g_s.acc[par][layer * 2 + 1][tid * 4], make_float4(a.x + b.x + c.x, a.y + b.y + c.y, a.z + b.z + c.z, a.w + b.w + c.w));
            }
            bar_comp();
            if (tid == 0) grid_arrive(layer * 2 + 1);
        }
        if (layer == 1 && cta != 0) return;
        if (tid == 0) grid_wait(layer * 2 + 1, (epoch + 1) * MLP_CTAS);
        bar_comp();
#pragma unroll
        for (int j = 0; j < 5; ++j) {
            float4 a = ldg_cg4(&g_s.acc[par][layer * 2 + 1][lane * 4 + 128 * j]);
            uint2 bb = *reinterpret_cast<const uint2*>(b2 + lane * 4 + 128 * j);
            xr[j * 4 + 0] = bf16r(xr[j * 4 + 0] + bf16r(bf16r(a.x) + bf_lo(bb.x)));
            xr[j * 4 + 1] = bf16r(xr[j * 4 + 1] + bf16r(bf16r(a.y) + bf_hi(bb.x)));
            xr[j * 4 + 2] = bf16r(xr[j * 4 + 2] + bf16r(bf16r(a.z) + bf_lo(bb.y)));
            xr[j * 4 + 3] = bf16r(xr[j * 4 + 3] + bf16r(bf16r(a.w) + bf_hi(bb.y)));
        }
    }
    if (warp == 0) {
#pragma unroll
        for (int j = 0; j < 5; ++j) {
            __nv_bfloat162 a = __floats2bfloat162_rn(xr[j * 4], xr[j * 4 + 1]);
            __nv_bfloat162 b = __floats2bfloat162_rn(xr[j * 4 + 2], xr[j * 4 + 3]);
            uint2 u;
            u.x = *reinterpret_cast<uint32_t*>(&a); u.y = *reinterpret_cast<uint32_t*>(&b);
            *reinterpret_cast<uint2*>(out + lane * 4 + 128 * j) = u;
        }
        if (lane == 0) asm volatile("st.relaxed.gpu.global.u32 [%0], %1;" ::"l"(&g_s.epoch), "r"(epoch + 1) : "memory");
    }
}

typedef CUresult (*EncodeFn)(CUtensorMap*, CUtensorMapDataType, cuuint32_t, void*, const cuuint64_t*, const cuuint64_t*,
                             const cuuint32_t*, const cuuint32_t*, CUtensorMapInterleave, CUtensorMapSwizzle,
                             CUtensorMapL2promotion, CUtensorMapFloatOOBfill);

void make_map(EncodeFn fn, CUtensorMap* tm, const void* ptr) {
    cuuint64_t gdim[2] = {(cuuint64_t)DH, (cuuint64_t)NHEAD * SK};
    cuuint64_t gstr[1] = {(cuuint64_t)DH * 2};
    cuuint32_t box[2] = {64, (cuuint32_t)TILE_KEYS};
    cuuint32_t estr[2] = {1, 1};
    fn(tm, CU_TENSOR_MAP_DATA_TYPE_BFLOAT16, 2, const_cast<void*>(ptr), gdim, gstr, box, estr,
       CU_TENSOR_MAP_INTERLEAVE_NONE, CU_TENSOR_MAP_SWIZZLE_128B, CU_TENSOR_MAP_L2_PROMOTION_L2_256B,
       CU_TENSOR_MAP_FLOAT_OOB_FILL_NONE);
}

}

extern "C" void kernel_launch(void* const* d_in, const int* in_sizes, int n_in, void* d_out, int out_size) {
    static EncodeFn encode = nullptr;
    if (!encode) {
        void* fn = nullptr;
        cudaDriverEntryPointQueryResult st;
        cudaGetDriverEntryPoint("cuTensorMapEncodeTiled", &fn, cudaEnableDefault, &st);
        encode = (EncodeFn)fn;
        cudaFuncSetAttribute(fused_kernel, cudaFuncAttributeMaxDynamicSharedMemorySize, SM_TOTAL);
    }
    CUtensorMap tmK, tmV;
    make_map(encode, &tmK, d_in[1]);
    make_map(encode, &tmV, d_in[2]);
    fused_kernel<<<NCTA, NTHREADS, SM_TOTAL>>>(
        tmK, tmV, (const __nv_bfloat16*)d_in[0], (const __nv_bfloat16*)d_in[3], (const __nv_bfloat16*)d_in[4],
        (const __nv_bfloat16*)d_in[6], (const __nv_bfloat16*)d_in[7], (const __nv_bfloat16*)d_in[8],
        (const __nv_bfloat16*)d_in[9], (__nv_bfloat16*)d_out);
}
```

```cpp
#include <cuda_runtime.h>
#include <cuda_bf16.h>
#include <cuda.h>
#include <stdint.h>

namespace {

constexpr int D_MODEL = 640;
constexpr int NHEAD = 32;
constexpr int SK = 4096;
constexpr int DH = 128;
constexpr int FF = 1728;
constexpr int NCTA = 128;
constexpr int TILE_KEYS = 64;
constexpr int TILE_BYTES = TILE_KEYS * DH * 2;
constexpr int NT = 16;
constexpr int NSLOT = 13;
constexpr int RETAIN = 10;
constexpr int NCOMP = 256;
constexpr int NTHREADS = NCOMP + 128;
#define VREG_N 3
constexpr int KREG = 16 - NSLOT;
constexpr int VREG = VREG_N;
constexpr int MLP_CTAS = FF / 16;
constexpr int SPIN_LIMIT = 1 << 22;
constexpr int NREP = 8;
#define INFLIGHT 3
#define NPRE 2

__host__ __device__ constexpr int slot1(int n) { return n < RETAIN ? n : RETAIN + (n - RETAIN) % (NSLOT - RETAIN); }
__host__ __device__ constexpr int slot2(int c) { return (c & 15) < NSLOT ? (c & 15) : 0; }
static_assert(16 - VREG <= NSLOT, "pass-2 V tiles must fit the freed K slots");
__host__ __device__ constexpr unsigned long long pack_slots(int pass, int base) {
    unsigned long long v = 0;
    for (int i = 0; i < 16; ++i) v |= (unsigned long long)(pass == 0 ? slot1(base + i) : slot2(base + i)) << (4 * i);
    return v;
}
constexpr unsigned long long SLOTS_K0 = pack_slots(0, 0), SLOTS_V0 = pack_slots(0, 16);
constexpr unsigned long long SLOTS_K1 = pack_slots(1, 0), SLOTS_V1 = pack_slots(1, 16);

constexpr int SM_SLOTS = 0;
constexpr int SM_A = NSLOT * TILE_BYTES;
constexpr int SM_B = SM_A + 8192;
constexpr int SM_P = SM_B + 2048;
constexpr int SM_XN = SM_B + 4096;
constexpr int SM_XS = SM_XN + 2560;
constexpr int SM_MISC = SM_XS + 2560;
constexpr int SM_BAR = SM_MISC + 1024;
constexpr int SM_TAB = SM_BAR + 256;
constexpr int SM_TOTAL = SM_TAB + 64;
static_assert(SM_TOTAL <= 232448, "smem");

struct Scratch {
    unsigned epoch;
    unsigned pad0[31];
    unsigned cnt[4 * 32];
    float acc[2][4][NREP][D_MODEL];
    unsigned long long qx[2][NCTA][DH];
    unsigned long long ox[2][NCTA][DH + 8];
};
__device__ Scratch g_s;
#define TS(i)
#define FAIL(code) __trap()
#define ABORTED() false

__device__ __forceinline__ float bf16r(float x) { return __bfloat162float(__float2bfloat16_rn(x)); }
__device__ __forceinline__ float bf_lo(unsigned u) { return __uint_as_float(u << 16); }
__device__ __forceinline__ float bf_hi(unsigned u) { return __uint_as_float(u & 0xffff0000u); }
__device__ __forceinline__ uint32_t smem_u32(const void* p) { return (uint32_t)__cvta_generic_to_shared(p); }

__device__ __forceinline__ void bar_comp() { asm volatile("bar.sync 1, 256;" ::: "memory"); }

__device__ __forceinline__ void mbar_init(uint32_t bar, int count) {
    asm volatile("mbarrier.init.shared::cta.b64 [%0], %1;" ::"r"(bar), "r"(count) : "memory");
}
__device__ __forceinline__ void mbar_arrive(uint32_t bar) {
    asm volatile("mbarrier.arrive.shared::cta.b64 _, [%0];" ::"r"(bar) : "memory");
}
__device__ __forceinline__ void mbar_expect_tx(uint32_t bar, int bytes) {
    asm volatile("mbarrier.arrive.expect_tx.shared::cta.b64 _, [%0], %1;" ::"r"(bar), "r"(bytes) : "memory");
}
__device__ __forceinline__ void mbar_wait(uint32_t bar, uint32_t parity, int code = 1) {
    uint32_t done = 0;
#pragma unroll 1
    for (int it = 0; it < SPIN_LIMIT; ++it) {
        if (ABORTED()) return;
        asm volatile(
            "{\n.reg .pred p;\n"
            "mbarrier.try_wait.parity.shared::cta.b64 p, [%1], %2;\n"
            "selp.u32 %0, 1, 0, p;\n}\n"
            : "=r"(done) : "r"(bar), "r"(parity) : "memory");
        if (done) return;
    }
    FAIL(code);
}
__device__ __forceinline__ void tma_load_2d(uint32_t dst, const CUtensorMap* tm, int c0, int c1, uint32_t bar,
                                            unsigned long long policy) {
    asm volatile(
        "cp.async.bulk.tensor.2d.shared::cluster.global.mbarrier::complete_tx::bytes.L2::cache_hint "
        "[%0], [%1, {%3, %4}], [%2], %5;"
        ::"r"(dst), "l"((unsigned long long)tm), "r"(bar), "r"(c0), "r"(c1), "l"(policy) : "memory");
}
__device__ __forceinline__ void ldsm_x4(uint32_t addr, uint32_t* r) {
    asm volatile("ldmatrix.sync.aligned.m8n8.x4.shared.b16 {%0,%1,%2,%3}, [%4];"
                 : "=r"(r[0]), "=r"(r[1]), "=r"(r[2]), "=r"(r[3]) : "r"(addr) : "memory");
}
__device__ __forceinline__ void ldsm_x4_t(uint32_t addr, uint32_t* r) {
    asm volatile("ldmatrix.sync.aligned.m8n8.x4.trans.shared.b16 {%0,%1,%2,%3}, [%4];"
                 : "=r"(r[0]), "=r"(r[1]), "=r"(r[2]), "=r"(r[3]) : "r"(addr) : "memory");
}
#define LDSM4(TRANS, a, t0, off)                                                                                   \
    asm volatile(                                                                                                   \
        "ldmatrix.sync.aligned.m8n8.x4" TRANS ".shared.b16 {%0,%1,%2,%3}, [%16];\n"                                 \
        "ldmatrix.sync.aligned.m8n8.x4" TRANS ".shared.b16 {%4,%5,%6,%7}, [%17];\n"                                 \
        "ldmatrix.sync.aligned.m8n8.x4" TRANS ".shared.b16 {%8,%9,%10,%11}, [%18];\n"                               \
        "ldmatrix.sync.aligned.m8n8.x4" TRANS ".shared.b16 {%12,%13,%14,%15}, [%19];\n"                             \
        : "=r"(a[0][0]), "=r"(a[0][1]), "=r"(a[0][2]), "=r"(a[0][3]), "=r"(a[1][0]), "=r"(a[1][1]), "=r"(a[1][2]), \
          "=r"(a[1][3]), "=r"(a[2][0]), "=r"(a[2][1]), "=r"(a[2][2]), "=r"(a[2][3]), "=r"(a[3][0]), "=r"(a[3][1]), \
          "=r"(a[3][2]), "=r"(a[3][3])                                                                              \
        : "r"((t0) + off[0]), "r"((t0) + off[1]), "r"((t0) + off[2]), "r"((t0) + off[3])                            \
        : "memory")
__device__ __forceinline__ void mma_bf16(float* c, const uint32_t* a, uint32_t b0, uint32_t b1) {
    asm volatile(
        "mma.sync.aligned.m16n8k16.row.col.f32.bf16.bf16.f32 {%0,%1,%2,%3}, {%4,%5,%6,%7}, {%8,%9}, {%0,%1,%2,%3};"
        : "+f"(c[0]), "+f"(c[1]), "+f"(c[2]), "+f"(c[3])
        : "r"(a[0]), "r"(a[1]), "r"(a[2]), "r"(a[3]), "r"(b0), "r"(b1));
}
__device__ __forceinline__ void ll_store(unsigned long long* p, float v, unsigned tag) {
    unsigned long long w = ((unsigned long long)tag << 32) | (unsigned long long)__float_as_uint(v);
    asm volatile("st.relaxed.gpu.global.u64 [%0], %1;" ::"l"(p), "l"(w) : "memory");
}
__device__ __forceinline__ float ll_wait(const unsigned long long* p, unsigned tag, int code = 2) {
    unsigned long long w;
#pragma unroll 1
    for (int it = 0; it < SPIN_LIMIT; ++it) {
        if (ABORTED()) return 0.f;
        asm volatile("ld.relaxed.gpu.global.u64 %0, [%1];" : "=l"(w) : "l"(p) : "memory");
        if ((unsigned)(w >> 32) == tag) return __uint_as_float((unsigned)w);
    }
    FAIL(code);
    return 0.f;
}
__device__ __forceinline__ unsigned long long ld_rlx64(const unsigned long long* p) {
    unsigned long long w;
    asm volatile("ld.relaxed.gpu.global.u64 %0, [%1];" : "=l"(w) : "l"(p) : "memory");
    return w;
}
__device__ __forceinline__ void ll_wait4(const unsigned long long* p, int stride, unsigned tag, float* v, int code = 2) {
#pragma unroll 1
    for (int it = 0; it < SPIN_LIMIT; ++it) {
        if (ABORTED()) return;
        const unsigned long long w0 = ld_rlx64(p), w1 = ld_rlx64(p + stride), w2 = ld_rlx64(p + 2 * stride), w3 = ld_rlx64(p + 3 * stride);
        if ((unsigned)(w0 >> 32) == tag && (unsigned)(w1 >> 32) == tag && (unsigned)(w2 >> 32) == tag && (unsigned)(w3 >> 32) == tag) {
            v[0] = __uint_as_float((unsigned)w0); v[1] = __uint_as_float((unsigned)w1);
            v[2] = __uint_as_float((unsigned)w2); v[3] = __uint_as_float((unsigned)w3);
            return;
        }
    }
    FAIL(code);
}
__device__ __forceinline__ void ll_wait4x2(const unsigned long long* p, const unsigned long long* q, int stride, unsigned tag,
                                           float* v, float* u, int code = 2) {
#pragma unroll 1
    for (int it = 0; it < SPIN_LIMIT; ++it) {
        if (ABORTED()) return;
        unsigned long long w[8];
#pragma unroll
        for (int i = 0; i < 4; ++i) { w[i] = ld_rlx64(p + i * stride); w[4 + i] = ld_rlx64(q + i * stride); }
        bool ok = true;
#pragma unroll
        for (int i = 0; i < 8; ++i) ok = ok && ((unsigned)(w[i] >> 32) == tag);
        if (ok) {
#pragma unroll
            for (int i = 0; i < 4; ++i) { v[i] = __uint_as_float((unsigned)w[i]); u[i] = __uint_as_float((unsigned)w[4 + i]); }
            return;
        }
    }
    FAIL(code);
}
__device__ __forceinline__ uint4 ldg_nc(const void* p) {
    uint4 v;
    asm volatile("ld.global.nc.L1::no_allocate.v4.u32 {%0,%1,%2,%3}, [%4];"
                 : "=r"(v.x), "=r"(v.y), "=r"(v.z), "=r"(v.w) : "l"(p));
    return v;
}
__device__ __forceinline__ uint4 ldg_nc_ef(const void* p, unsigned long long pol) {
    uint4 v;
    asm volatile("ld.global.nc.L1::no_allocate.L2::cache_hint.v4.u32 {%0,%1,%2,%3}, [%4], %5;"
                 : "=r"(v.x), "=r"(v.y), "=r"(v.z), "=r"(v.w) : "l"(p), "l"(pol));
    return v;
}
__device__ __forceinline__ float4 ldg_cg4(const float* p) {
    float4 v;
    asm volatile("ld.relaxed.gpu.global.v4.f32 {%0,%1,%2,%3}, [%4];"
                 : "=f"(v.x), "=f"(v.y), "=f"(v.z), "=f"(v.w) : "l"(p) : "memory");
    return v;
}
__device__ __forceinline__ void red_add4(float* p, float4 v) {
    asm volatile("red.relaxed.gpu.global.add.v4.f32 [%0], {%1,%2,%3,%4};"
                 ::"l"(p), "f"(v.x), "f"(v.y), "f"(v.z), "f"(v.w) : "memory");
}
__device__ __forceinline__ void fma8(float* acc, float s, const uint4& w) {
    acc[0] = fmaf(s, bf_lo(w.x), acc[0]); acc[1] = fmaf(s, bf_hi(w.x), acc[1]);
    acc[2] = fmaf(s, bf_lo(w.y), acc[2]); acc[3] = fmaf(s, bf_hi(w.y), acc[3]);
    acc[4] = fmaf(s, bf_lo(w.z), acc[4]); acc[5] = fmaf(s, bf_hi(w.z), acc[5]);
    acc[6] = fmaf(s, bf_lo(w.w), acc[6]); acc[7] = fmaf(s, bf_hi(w.w), acc[7]);
}
__device__ __forceinline__ float warp_sum(float v) {
#pragma unroll
    for (int o = 16; o > 0; o >>= 1) v += __shfl_xor_sync(0xffffffffu, v, o);
    return v;
}
__device__ __forceinline__ float warp_max(float v) {
#pragma unroll
    for (int o = 16; o > 0; o >>= 1) v = fmaxf(v, __shfl_xor_sync(0xffffffffu, v, o));
    return v;
}
__device__ __noinline__ void layernorm_block(const float* src, float* dst, float* red, int tid) {
    const int warp = tid >> 5, lane = tid & 31;
    const bool has2 = tid < 128;
    const float v0 = src[tid], v1 = src[tid + 256], v2 = has2 ? src[tid + 512] : 0.f;
    float s = warp_sum(v0 + v1 + v2);
    if (lane == 0) red[warp] = s;
    bar_comp();
    float4 r0 = *reinterpret_cast<const float4*>(red), r1 = *reinterpret_cast<const float4*>(red + 4);
    const float mean = (((r0.x + r0.y) + (r0.z + r0.w)) + ((r1.x + r1.y) + (r1.z + r1.w))) * (1.0f / D_MODEL);
    const float d0 = v0 - mean, d1 = v1 - mean, d2 = has2 ? v2 - mean : 0.f;
    s = warp_sum(fmaf(d0, d0, fmaf(d1, d1, d2 * d2)));
    if (lane == 0) red[8 + warp] = s;
    bar_comp();
    r0 = *reinterpret_cast<const float4*>(red + 8); r1 = *reinterpret_cast<const float4*>(red + 12);
    const float var = (((r0.x + r0.y) + (r0.z + r0.w)) + ((r1.x + r1.y) + (r1.z + r1.w))) * (1.0f / D_MODEL);
    const float mb = bf16r(mean);
    const float den = bf16r(sqrtf(bf16r(bf16r(var) + 1e-5f)));
    dst[tid] = bf16r(__fdiv_rn(bf16r(v0 - mb), den));
    dst[tid + 256] = bf16r(__fdiv_rn(bf16r(v1 - mb), den));
    if (has2) dst[tid + 512] = bf16r(__fdiv_rn(bf16r(v2 - mb), den));
    bar_comp();
}

__device__ __forceinline__ void grid_arrive(int ph) {
    asm volatile("red.release.gpu.global.add.u32 [%0], 1;" ::"l"(&g_s.cnt[ph * 32]) : "memory");
}
__device__ __forceinline__ void grid_wait(int ph, unsigned target) {
    unsigned v;
#pragma unroll 1
    for (int it = 0; it < SPIN_LIMIT; ++it) {
        if (ABORTED()) return;
        asm volatile("ld.acquire.gpu.global.u32 %0, [%1];" : "=r"(v) : "l"(&g_s.cnt[ph * 32]) : "memory");
        if ((int)(v - target) >= 0) return;
    }
    FAIL(3 + ph);
}

__global__ void __launch_bounds__(NTHREADS, 1)
fused_kernel(const __grid_constant__ CUtensorMap tmK, const __grid_constant__ CUtensorMap tmV,
             const __nv_bfloat16* __restrict__ x_in, const __nv_bfloat16* __restrict__ wq,
             const __nv_bfloat16* __restrict__ wo, const __nv_bfloat16* __restrict__ w1,
             const __nv_bfloat16* __restrict__ b1, const __nv_bfloat16* __restrict__ w2,
             const __nv_bfloat16* __restrict__ b2, __nv_bfloat16* __restrict__ out) {
    extern __shared__ __align__(1024) unsigned char smem[];
    const int tid = threadIdx.x;
    const int warp = tid >> 5;
    const int lane = tid & 31;
    const int cta = blockIdx.x;
    const int head = cta >> 2;
    const int quarter = cta & 3;
    const uint32_t sbase = smem_u32(smem);
    const uint32_t bar_full = sbase + SM_BAR;
    const uint32_t bar_empty = sbase + SM_BAR + NSLOT * 8;
    const uint32_t bar_go = sbase + SM_BAR + 2 * NSLOT * 8;

    uint4 wv[11];
    const __nv_bfloat16* wq_p = wq + (size_t)(quarter * 160 + (tid >> 4)) * (NHEAD * DH) + head * DH + (tid & 15) * 8;
    unsigned long long pol_ef;
    asm volatile("createpolicy.fractional.L2::evict_first.b64 %0, 1.0;" : "=l"(pol_ef));
    if (warp < 8) {
#pragma unroll
        for (int i = 0; i < 10; ++i) wv[i] = ldg_nc_ef(wq_p + (size_t)(16 * i) * (NHEAD * DH), pol_ef);
    }
    if (tid == 0) {
        for (int s = 0; s < NSLOT; ++s) { mbar_init(bar_full + s * 8, 1); mbar_init(bar_empty + s * 8, 8); }
        mbar_init(bar_go, 8);
        asm volatile("fence.mbarrier_init.release.cluster;" ::: "memory");
    }
    __syncthreads();

    if (warp >= 8) {
        asm volatile("setmaxnreg.dec.sync.aligned.u32 24;");
        if (warp == 8 && lane == 0) {
            unsigned long long pol_first, pol_norm;
            asm volatile("createpolicy.fractional.L2::evict_first.b64 %0, 1.0;" : "=l"(pol_first));
            asm volatile("createpolicy.fractional.L2::evict_normal.b64 %0, 1.0;" : "=l"(pol_norm));
            const int row0 = head * SK + quarter * 1024;
            uint32_t used = 0, epar = 0, ppar = 0;
            int hist[INFLIGHT];
#pragma unroll
            for (int i = 0; i < INFLIGHT; ++i) hist[i] = -1;
#pragma unroll 1
            for (int n = 0; n < 64; ++n) {
                const int pass = n >> 5, t = n & 31;
                if (pass == 1 && (t < RETAIN || (t >= NSLOT && t < 16) || t >= 32 - VREG)) continue;
                if (n == NPRE) {
                    mbar_wait(bar_go, 0, 9);
                    asm volatile("cp.async.bulk.prefetch.L2.global.L2::cache_hint [%0], %1, %2;"
                                 ::"l"(wo + (size_t)(head * DH + quarter * 32) * D_MODEL), "r"(32 * D_MODEL * 2), "l"(pol_first) : "memory");
                    if (cta < MLP_CTAS)
                        asm volatile("cp.async.bulk.prefetch.L2.global [%0], %1;"
                                     ::"l"(w2 + (size_t)(cta * 16) * D_MODEL), "r"(16 * D_MODEL * 2) : "memory");
                }
                if (n == 32 + NSLOT + 3) {
                    asm volatile("cp.async.bulk.prefetch.L2.global.L2::cache_hint [%0], %1, %2;"
                                 ::"l"(wo + (size_t)(head * DH + quarter * 32) * D_MODEL), "r"(32 * D_MODEL * 2), "l"(pol_first) : "memory");
                }
                const unsigned long long tabv = (t < 16) ? (pass ? SLOTS_K1 : SLOTS_K0) : (pass ? SLOTS_V1 : SLOTS_V0);
                const int s = (int)(tabv >> (4 * (t & 15))) & 15;
                if (used & (1u << s)) { mbar_wait(bar_empty + s * 8, (epar >> s) & 1, 10 + n); epar ^= (1u << s); }
                used |= (1u << s);
                {
                    bool skip = hist[0] < 0 || (hist[0] & 15) == s;
#pragma unroll
                    for (int i = 1; i < INFLIGHT; ++i) skip = skip || ((hist[i] & 15) == (hist[0] & 15));
                    if (!skip && pass == 0) mbar_wait(bar_full + (hist[0] & 15) * 8, hist[0] >> 4, 8);
                }
#pragma unroll
                for (int i = 0; i + 1 < INFLIGHT; ++i) hist[i] = hist[i + 1];
                hist[INFLIGHT - 1] = s | (((ppar >> s) & 1) << 4);
                ppar ^= (1u << s);
                const CUtensorMap* tm = (t < 16) ? &tmK : &tmV;
                const int row = row0 + (t & 15) * TILE_KEYS;
                const unsigned long long pol = (pass == 1 || t < 16 || t >= 32 - VREG) ? pol_first : pol_norm;
                const uint32_t dst = sbase + SM_SLOTS + s * TILE_BYTES;
                mbar_expect_tx(bar_full + s * 8, TILE_BYTES);
                tma_load_2d(dst, tm, 0, row, bar_full + s * 8, pol);
                tma_load_2d(dst + TILE_BYTES / 2, tm, 64, row, bar_full + s * 8, pol);
            }
        }
        return;
    }

    asm volatile("setmaxnreg.inc.sync.aligned.u32 240;");
    float* scores = reinterpret_cast<float*>(smem + SM_A);
    __nv_bfloat16* pbf = reinterpret_cast<__nv_bfloat16*>(smem + SM_P);
    float* gscr = reinterpret_cast<float*>(smem + SM_A);
    float* redb = reinterpret_cast<float*>(smem + SM_B);
    float* xn_s = reinterpret_cast<float*>(smem + SM_XN);
    float* xs = reinterpret_cast<float*>(smem + SM_XS);
    float* misc = reinterpret_cast<float*>(smem + SM_MISC);
    const int g = lane >> 2, t4 = lane & 3;
    const int half = warp >> 2, grp = warp & 3;
    const int chunk = tid % 80, rg = tid / 80;

    TS(0);
    unsigned epoch;
    asm volatile("ld.relaxed.gpu.global.u32 %0, [%1];" : "=r"(epoch) : "l"(&g_s.epoch) : "memory");
    const int par = epoch & 1;
    if (tid < 160) {
        const uint2 u = *reinterpret_cast<const uint2*>(x_in + tid * 4);
        *reinterpret_cast<float4*>(xs + tid * 4) = make_float4(bf_lo(u.x), bf_hi(u.x), bf_lo(u.y), bf_hi(u.y));
    }
    bar_comp();

    uint32_t fpar = 0;
    uint32_t vr[VREG][4][4];
    uint32_t kr[KREG][4][4];

#pragma unroll 1
    for (int layer = 0; layer < 2; ++layer) {
        const unsigned tag = epoch * 2 + layer + 1;
        layernorm_block(xs, xn_s, misc, tid);
        TS(20 + layer * 16);
        {
            float acc[8];
#pragma unroll
            for (int i = 0; i < 8; ++i) acc[i] = 0.f;
#pragma unroll
            for (int i = 0; i < 10; ++i) fma8(acc, xn_s[quarter * 160 + (tid >> 4) + 16 * i], wv[i]);
            if (layer == 0) { __syncwarp(); if (lane == 0) mbar_arrive(bar_go); }
#pragma unroll
            for (int i = 0; i < 8; ++i) acc[i] += __shfl_xor_sync(0xffffffffu, acc[i], 16);
            if (lane < 16) {
                *reinterpret_cast<float4*>(redb + warp * 128 + lane * 8) = make_float4(acc[0], acc[1], acc[2], acc[3]);
                *reinterpret_cast<float4*>(redb + warp * 128 + lane * 8 + 4) = make_float4(acc[4], acc[5], acc[6], acc[7]);
            }
        }
        bar_comp();
        TS(21 + layer * 16);
        if (tid < 128) {
            float s = 0.f;
#pragma unroll
            for (int w = 0; w < 8; ++w) s += redb[w * 128 + tid];
            ll_store(&g_s.qx[layer][cta][tid], s, tag);
            float qp[4];
            ll_wait4(&g_s.qx[layer][head * 4][tid], DH, tag, qp, 20);
            reinterpret_cast<__nv_bfloat16*>(misc + 64)[tid] = __float2bfloat16_rn((qp[0] + qp[1]) + (qp[2] + qp[3]));
        } else if (layer == 0) {
            const int i = tid - 128;
            if (i < 40) *reinterpret_cast<float4*>(&g_s.acc[par ^ 1][0][0][0] + cta * 160 + i * 4) = make_float4(0.f, 0.f, 0.f, 0.f);
            if (cta < MLP_CTAS)
                for (int r = i; r < D_MODEL; r += 128)
                    asm volatile("prefetch.global.L2 [%0];" ::"l"(w1 + (size_t)r * FF + cta * 16));
        }
        bar_comp();
        TS(1 + layer * 8);
        uint32_t qb[8];
        {
            const uint32_t* qw = reinterpret_cast<const uint32_t*>(misc + 64) + half * 32;
#pragma unroll
            for (int kk = 0; kk < 4; ++kk) {
                qb[kk * 2] = (g == 0) ? qw[kk * 8 + t4] : 0u;
                qb[kk * 2 + 1] = (g == 0) ? qw[kk * 8 + 4 + t4] : 0u;
            }
        }
        {
            const int row = grp * 16 + (lane & 7) + ((lane >> 3) & 1) * 8;
            uint32_t off[4];
#pragma unroll
            for (int kk = 0; kk < 4; ++kk) off[kk] = sbase + SM_SLOTS + half * 8192 + row * 128 + (((kk * 2 + (lane >> 4)) ^ (row & 7)) << 4);
            const unsigned long long tab = layer ? SLOTS_K1 : SLOTS_K0;
            const int nres = layer ? RETAIN : 0;
            const int nkeep = layer ? 0 : RETAIN;
            float* sp = scores + half * 1024 + grp * 16 + g;
            uint32_t fa[4][4], fb[4][4];
#define K_LOAD(F, C) do { const int s_ = (int)(tab >> (4 * (C))) & 15; \
                if ((C) >= nres) { mbar_wait(bar_full + s_ * 8, (fpar >> s_) & 1, 80 + layer * 32 + (C)); fpar ^= (1u << s_); } \
                LDSM4("", F, s_ * TILE_BYTES, off); } while (0)
#define K_MMA(F, C) do { float c0[4] = {0.f, 0.f, 0.f, 0.f}, c1[4] = {0.f, 0.f, 0.f, 0.f}; \
                mma_bf16(c0, F[0], qb[0], qb[1]); mma_bf16(c1, F[1], qb[2], qb[3]); \
                mma_bf16(c0, F[2], qb[4], qb[5]); mma_bf16(c1, F[3], qb[6], qb[7]); \
                __syncwarp(); \
                if (lane == 0 && (C) >= nkeep) mbar_arrive(bar_empty + ((int)(tab >> (4 * (C))) & 15) * 8); \
                if (t4 == 0) { sp[(C) * 64] = c0[0] + c1[0]; sp[(C) * 64 + 8] = c0[2] + c1[2]; } } while (0)
#define K_MMA_NOREL(F, C) do { float c0[4] = {0.f, 0.f, 0.f, 0.f}, c1[4] = {0.f, 0.f, 0.f, 0.f}; \
                mma_bf16(c0, F[0], qb[0], qb[1]); mma_bf16(c1, F[1], qb[2], qb[3]); \
                mma_bf16(c0, F[2], qb[4], qb[5]); mma_bf16(c1, F[3], qb[6], qb[7]); \
                if (t4 == 0) { sp[(C) * 64] = c0[0] + c1[0]; sp[(C) * 64 + 8] = c0[2] + c1[2]; } } while (0)
            K_LOAD(fa, 0);
#pragma unroll 1
            for (int c = 0; c < NSLOT - 1; c += 2) {
                K_LOAD(fb, c + 1);
                K_MMA(fa, c);
                K_LOAD(fa, c + 2);
                K_MMA(fb, c + 1);
            }
            K_MMA(fa, NSLOT - 1);
            if (layer == 0) {
#pragma unroll
                for (int c = 0; c < KREG; ++c) K_LOAD(kr[c], NSLOT + c);
            }
#pragma unroll
            for (int c = 0; c < KREG; ++c) { if (layer == 0) K_MMA(kr[c], NSLOT + c); else K_MMA_NOREL(kr[c], NSLOT + c); }
        }
        bar_comp();
        TS(2 + layer * 8);
        {
            const __nv_bfloat16* wp = wo + (size_t)(head * DH + quarter * 32 + rg) * D_MODEL + chunk * 8;
#pragma unroll
            for (int i = 0; i < 11; ++i)
                if (tid < 240 && rg + 3 * i < 32) wv[i] = ldg_nc_ef(wp + (size_t)(3 * i) * D_MODEL, pol_ef);
        }
        float sc[4];
        {
            const float4 s0 = *reinterpret_cast<const float4*>(scores + tid * 4);
            const float4 s1 = *reinterpret_cast<const float4*>(scores + 1024 + tid * 4);
            sc[0] = bf16r(bf16r(s0.x + s1.x) * 0.08838834764831845f);
            sc[1] = bf16r(bf16r(s0.y + s1.y) * 0.08838834764831845f);
            sc[2] = bf16r(bf16r(s0.z + s1.z) * 0.08838834764831845f);
            sc[3] = bf16r(bf16r(s0.w + s1.w) * 0.08838834764831845f);
            const float wmax = warp_max(fmaxf(fmaxf(sc[0], sc[1]), fmaxf(sc[2], sc[3])));
            if (lane == 0) misc[warp] = wmax;
        }
        bar_comp();
        float mloc;
        {
            const float4 r0 = *reinterpret_cast<const float4*>(misc), r1 = *reinterpret_cast<const float4*>(misc + 4);
            mloc = fmaxf(fmaxf(fmaxf(r0.x, r0.y), fmaxf(r0.z, r0.w)), fmaxf(fmaxf(r1.x, r1.y), fmaxf(r1.z, r1.w)));
            const float e0 = __expf(sc[0] - mloc), e1 = __expf(sc[1] - mloc), e2 = __expf(sc[2] - mloc), e3 = __expf(sc[3] - mloc);
            __nv_bfloat162 p01 = __floats2bfloat162_rn(e0, e1), p23 = __floats2bfloat162_rn(e2, e3);
            uint2 pk;
            pk.x = *reinterpret_cast<uint32_t*>(&p01); pk.y = *reinterpret_cast<uint32_t*>(&p23);
            *reinterpret_cast<uint2*>(pbf + tid * 4) = pk;
            float ls = warp_sum((e0 + e1) + (e2 + e3));
            if (lane == 0) misc[8 + warp] = ls;
        }
        bar_comp();
        float oa[4][4];
#pragma unroll
        for (int dd = 0; dd < 4; ++dd) { oa[dd][0] = oa[dd][1] = oa[dd][2] = oa[dd][3] = 0.f; }
        {
            const int key = grp * 16 + (lane & 7) + (lane >> 4) * 8;
            uint32_t off[4];
#pragma unroll
            for (int dd = 0; dd < 4; ++dd) off[dd] = sbase + SM_SLOTS + half * 8192 + key * 128 + (((dd * 2 + ((lane >> 3) & 1)) ^ (key & 7)) << 4);
            const uint32_t* pw0 = reinterpret_cast<const uint32_t*>(pbf + grp * 16) + t4;
            const unsigned long long tab = layer ? SLOTS_V1 : SLOTS_V0;
#define V_LOAD(F, C) do { const int s_ = (int)(tab >> (4 * (C))) & 15; \
                mbar_wait(bar_full + s_ * 8, (fpar >> s_) & 1, 96 + layer * 32 + (C)); fpar ^= (1u << s_); \
                LDSM4(".trans", F, s_ * TILE_BYTES, off); } while (0)
#define V_MMA(F, C) do { const uint32_t b0_ = (g == 0) ? pw0[(C) * 32] : 0u, b1_ = (g == 0) ? pw0[(C) * 32 + 4] : 0u; \
                mma_bf16(oa[0], F[0], b0_, b1_); mma_bf16(oa[1], F[1], b0_, b1_); \
                mma_bf16(oa[2], F[2], b0_, b1_); mma_bf16(oa[3], F[3], b0_, b1_); } while (0)
#define V_REL(C) do { __syncwarp(); if (lane == 0) mbar_arrive(bar_empty + ((int)(tab >> (4 * (C))) & 15) * 8); } while (0)
            if (layer == 1) {
#pragma unroll
                for (int c = 0; c < VREG; ++c) V_MMA(vr[c], 16 - VREG + c);
            }
            uint32_t fa[4][4], fb[4][4];
            constexpr int NV = 16 - VREG;
            V_LOAD(fa, 0);
#pragma unroll 1
            for (int c = 0; c + 1 < NV; c += 2) {
                V_LOAD(fb, c + 1);
                V_MMA(fa, c); V_REL(c);
                if (c + 2 < NV) V_LOAD(fa, c + 2);
                V_MMA(fb, c + 1); V_REL(c + 1);
            }
            if (NV & 1) { V_MMA(fa, NV - 1); V_REL(NV - 1); }
            if (layer == 0) {
#pragma unroll
                for (int c = 0; c < VREG; ++c) {
                    V_LOAD(vr[c], 16 - VREG + c);
                    V_MMA(vr[c], 16 - VREG + c); V_REL(16 - VREG + c);
                }
            }
        }
        TS(3 + layer * 8);
        if (t4 == 0) {
#pragma unroll
            for (int dd = 0; dd < 4; ++dd) {
                redb[grp * 128 + half * 64 + dd * 16 + g] = oa[dd][0];
                redb[grp * 128 + half * 64 + dd * 16 + g + 8] = oa[dd][2];
            }
        }
        bar_comp();
        if (tid < 128) {
            float s = (redb[tid] + redb[128 + tid]) + (redb[256 + tid] + redb[384 + tid]);
            ll_store(&g_s.ox[layer][cta][tid], s, tag);
        } else if (tid < 130) {
            const float4 r0 = *reinterpret_cast<const float4*>(misc + 8), r1 = *reinterpret_cast<const float4*>(misc + 12);
            const float lloc = ((r0.x + r0.y) + (r0.z + r0.w)) + ((r1.x + r1.y) + (r1.z + r1.w));
            ll_store(&g_s.ox[layer][cta][tid], tid == 128 ? mloc : lloc, tag);
        }
        if (warp == 7) {
            float op[4], ms[4];
            ll_wait4x2(&g_s.ox[layer][head * 4][quarter * 32 + lane], &g_s.ox[layer][head * 4][128 + (lane & 1)], DH + 8, tag, op, ms, 21);
            float mm[4], ll[4];
#pragma unroll
            for (int pp = 0; pp < 4; ++pp) { mm[pp] = __shfl_sync(0xffffffffu, ms[pp], 0); ll[pp] = __shfl_sync(0xffffffffu, ms[pp], 1); }
            const float M = fmaxf(fmaxf(mm[0], mm[1]), fmaxf(mm[2], mm[3]));
            float L = 0.f, o = 0.f;
#pragma unroll
            for (int pp = 0; pp < 4; ++pp) { const float wgt = __expf(mm[pp] - M); L = fmaf(ll[pp], wgt, L); o = fmaf(op[pp], wgt, o); }
            misc[32 + lane] = bf16r(__fdiv_rn(o, L));
        }
        bar_comp();
        TS(4 + layer * 8);
        int nrows = 32;
#pragma unroll 1
        for (int sub = 0; sub < 2; ++sub) {
            const int ph = layer * 2 + sub;
            if (tid < 240) {
                float acc[8];
#pragma unroll
                for (int i = 0; i < 8; ++i) acc[i] = 0.f;
#pragma unroll
                for (int i = 0; i < 11; ++i)
                    if (rg + 3 * i < nrows) fma8(acc, misc[32 + rg + 3 * i], wv[i]);
                *reinterpret_cast<float4*>(gscr + rg * 640 + chunk * 8) = make_float4(acc[0], acc[1], acc[2], acc[3]);
                *reinterpret_cast<float4*>(gscr + rg * 640 + chunk * 8 + 4) = make_float4(acc[4], acc[5], acc[6], acc[7]);
            }
            bar_comp();
            TS(22 + sub * 4 + layer * 16);
            if (tid < 160 && nrows > 0) {
                float4 a = *reinterpret_cast<const float4*>(gscr + tid * 4);
                float4 b = *reinterpret_cast<const float4*>(gscr + 640 + tid * 4);
                float4 c = *reinterpret_cast<const float4*>(gscr + 1280 + tid * 4);
                red_add4(&g_s.acc[par][ph][cta % NREP][tid * 4], make_float4(a.x + b.x + c.x, a.y + b.y + c.y, a.z + b.z + c.z, a.w + b.w + c.w));
            }
            bar_comp();
            TS(23 + sub * 4 + layer * 16);
            if (tid == 0) grid_arrive(ph);
            TS(5 + sub * 2 + layer * 8);
            if (ph == 3 && cta != 0) return;
            if (ph == 0 && tid < 160) {
                const __nv_bfloat16* pp = wq + (size_t)(quarter * 160 + tid) * (NHEAD * DH) + head * DH;
                asm volatile("prefetch.global.L2 [%0];" ::"l"(pp));
                asm volatile("prefetch.global.L2 [%0];" ::"l"(pp + 64));
            }
            uint4 w1v[5];
            float bv = 0.f;
            if (sub == 0) {
                if (cta < MLP_CTAS) {
                    const __nv_bfloat16* wp = w1 + (size_t)(tid >> 1) * FF + cta * 16 + (tid & 1) * 8;
#pragma unroll
                    for (int i = 0; i < 5; ++i) w1v[i] = ldg_nc(wp + (size_t)(128 * i) * FF);
                    const __nv_bfloat16* wp2 = w2 + (size_t)(cta * 16 + rg) * D_MODEL + chunk * 8;
#pragma unroll
                    for (int i = 0; i < 6; ++i)
                        if (tid < 240 && rg + 3 * i < 16) wv[i] = ldg_nc(wp2 + (size_t)(3 * i) * D_MODEL);
                    if (tid < 16) bv = __bfloat162float(b1[cta * 16 + tid]);
                }
            } else if (layer == 0) {
#pragma unroll
                for (int i = 0; i < 10; ++i) wv[i] = ldg_nc_ef(wq_p + (size_t)(16 * i) * (NHEAD * DH), pol_ef);
            }
            if (tid < 160) {
                uint2 bb = make_uint2(0u, 0u);
                if (sub == 1) bb = *reinterpret_cast<const uint2*>(b2 + tid * 4);
                grid_wait(ph, (epoch + 1) * NCTA);
                float4 v[NREP];
#pragma unroll
                for (int r = 0; r < NREP; ++r) v[r] = ldg_cg4(&g_s.acc[par][ph][r][tid * 4]);
                float4 s = v[0];
#pragma unroll
                for (int r = 1; r < NREP; ++r) { s.x += v[r].x; s.y += v[r].y; s.z += v[r].z; s.w += v[r].w; }
                s.x = bf16r(s.x); s.y = bf16r(s.y); s.z = bf16r(s.z); s.w = bf16r(s.w);
                if (sub == 1) {
                    s.x = bf16r(s.x + bf_lo(bb.x)); s.y = bf16r(s.y + bf_hi(bb.x));
                    s.z = bf16r(s.z + bf_lo(bb.y)); s.w = bf16r(s.w + bf_hi(bb.y));
                }
                float4 x = *reinterpret_cast<const float4*>(xs + tid * 4);
                x.x = bf16r(x.x + s.x); x.y = bf16r(x.y + s.y); x.z = bf16r(x.z + s.z); x.w = bf16r(x.w + s.w);
                *reinterpret_cast<float4*>(xs + tid * 4) = x;
            }
            bar_comp();
            TS(6 + sub * 2 + layer * 8);
            if (sub == 0) {
                nrows = 0;
                if (cta < MLP_CTAS) {
                    nrows = 16;
                    layernorm_block(xs, xn_s, misc, tid);
                    layernorm_block(xn_s, xn_s, misc, tid);
                    TS(24 + layer * 16);
                    float acc[8];
#pragma unroll
                    for (int i = 0; i < 8; ++i) acc[i] = 0.f;
#pragma unroll
                    for (int i = 0; i < 5; ++i) fma8(acc, xn_s[(tid >> 1) + 128 * i], w1v[i]);
#pragma unroll
                    for (int o = 2; o <= 16; o <<= 1)
#pragma unroll
                        for (int i = 0; i < 8; ++i) acc[i] += __shfl_xor_sync(0xffffffffu, acc[i], o);
                    if (lane < 2) {
                        *reinterpret_cast<float4*>(redb + warp * 16 + lane * 8) = make_float4(acc[0], acc[1], acc[2], acc[3]);
                        *reinterpret_cast<float4*>(redb + warp * 16 + lane * 8 + 4) = make_float4(acc[4], acc[5], acc[6], acc[7]);
                    }
                    bar_comp();
                    TS(25 + layer * 16);
                    if (tid < 16) {
                        float s = 0.f;
#pragma unroll
                        for (int w = 0; w < 8; ++w) s += redb[w * 16 + tid];
                        const float u = bf16r(bf16r(s) + bv);
                        const float inner = 0.7978845608028654f * (u + 0.044715f * u * u * u);
                        misc[32 + tid] = bf16r(0.5f * u * (1.0f + tanhf(inner)));
                    }
                    bar_comp();
                }
            }
        }
    }
    if (tid < 160) {
        const float4 x = *reinterpret_cast<const float4*>(xs + tid * 4);
        __nv_bfloat162 a = __floats2bfloat162_rn(x.x, x.y);
        __nv_bfloat162 b = __floats2bfloat162_rn(x.z, x.w);
        uint2 u;
        u.x = *reinterpret_cast<uint32_t*>(&a); u.y = *reinterpret_cast<uint32_t*>(&b);
        *reinterpret_cast<uint2*>(out + tid * 4) = u;
        if (tid == 0) asm volatile("st.relaxed.gpu.global.u32 [%0], %1;" ::"l"(&g_s.epoch), "r"(epoch + 1) : "memory");
    }
}

typedef CUresult (*EncodeFn)(CUtensorMap*, CUtensorMapDataType, cuuint32_t, void*, const cuuint64_t*, const cuuint64_t*,
                             const cuuint32_t*, const cuuint32_t*, CUtensorMapInterleave, CUtensorMapSwizzle,
                             CUtensorMapL2promotion, CUtensorMapFloatOOBfill);

void make_map(EncodeFn fn, CUtensorMap* tm, const void* ptr) {
    cuuint64_t gdim[2] = {(cuuint64_t)DH, (cuuint64_t)NHEAD * SK};
    cuuint64_t gstr[1] = {(cuuint64_t)DH * 2};
    cuuint32_t box[2] = {64, (cuuint32_t)TILE_KEYS};
    cuuint32_t estr[2] = {1, 1};
    fn(tm, CU_TENSOR_MAP_DATA_TYPE_BFLOAT16, 2, const_cast<void*>(ptr), gdim, gstr, box, estr,
       CU_TENSOR_MAP_INTERLEAVE_NONE, CU_TENSOR_MAP_SWIZZLE_128B, CU_TENSOR_MAP_L2_PROMOTION_L2_256B,
       CU_TENSOR_MAP_FLOAT_OOB_FILL_NONE);
}

}

extern "C" void kernel_launch(void* const* d_in, const int* in_sizes, int n_in, void* d_out, int out_size) {
    static EncodeFn encode = nullptr;
    if (!encode) {
        void* fn = nullptr;
        cudaDriverEntryPointQueryResult st;
        cudaGetDriverEntryPoint("cuTensorMapEncodeTiled", &fn, cudaEnableDefault, &st);
        encode = (EncodeFn)fn;
        cudaFuncSetAttribute(fused_kernel, cudaFuncAttributeMaxDynamicSharedMemorySize, SM_TOTAL);
    }
    CUtensorMap tmK, tmV;
    make_map(encode, &tmK, d_in[1]);
    make_map(encode, &tmV, d_in[2]);
    fused_kernel<<<NCTA, NTHREADS, SM_TOTAL>>>(
        tmK, tmV, (const __nv_bfloat16*)d_in[0], (const __nv_bfloat16*)d_in[3], (const __nv_bfloat16*)d_in[4],
        (const __nv_bfloat16*)d_in[6], (const __nv_bfloat16*)d_in[7], (const __nv_bfloat16*)d_in[8],
        (const __nv_bfloat16*)d_in[9], (__nv_bfloat16*)d_out);
}
```

```cpp
#include <cuda_runtime.h>
#include <cuda_bf16.h>
#include <cuda.h>
#include <stdint.h>

namespace {

constexpr int D_MODEL = 640;
constexpr int NHEAD = 32;
constexpr int SK = 4096;
constexpr int DH = 128;
constexpr int FF = 1728;
constexpr int NCTA = 128;
constexpr int TILE_KEYS = 64;
constexpr int TILE_BYTES = TILE_KEYS * DH * 2;
constexpr int NSLOT = 13;
constexpr int RETAIN = 10;
constexpr int NCOMP = 256;
constexpr int NTHREADS = NCOMP + 128;
constexpr int KREG = 16 - NSLOT;
constexpr int VREG = 3;
constexpr int MLP_CTAS = FF / 16;
constexpr int SPIN_LIMIT = 1 << 22;
constexpr int NVEC = 214;
constexpr int NREP = 4;
constexpr int INFLIGHT = 3;
constexpr int NPRE = 2;

__host__ __device__ constexpr int slot1(int n) { return n < RETAIN ? n : RETAIN + (n - RETAIN) % (NSLOT - RETAIN); }
__host__ __device__ constexpr int slot2(int c) { return (c & 15) < NSLOT ? (c & 15) : 0; }
static_assert(16 - VREG <= NSLOT, "pass-2 V tiles must fit the freed K slots");
__host__ __device__ constexpr unsigned long long pack_slots(int pass, int base) {
    unsigned long long v = 0;
    for (int i = 0; i < 16; ++i) v |= (unsigned long long)(pass == 0 ? slot1(base + i) : slot2(base + i)) << (4 * i);
    return v;
}
constexpr unsigned long long SLOTS_K0 = pack_slots(0, 0), SLOTS_V0 = pack_slots(0, 16);
constexpr unsigned long long SLOTS_K1 = pack_slots(1, 0), SLOTS_V1 = pack_slots(1, 16);

constexpr int SM_SLOTS = 0;
constexpr int SM_A = NSLOT * TILE_BYTES;
constexpr int SM_B = SM_A + 8192;
constexpr int SM_P = SM_B + 2048;
constexpr int SM_XN = SM_B + 4096;
constexpr int SM_XS = SM_XN + 2560;
constexpr int SM_MISC = SM_XS + 2560;
constexpr int SM_BAR = SM_MISC + 1024;
constexpr int SM_TOTAL = SM_BAR + 256;
static_assert(SM_TOTAL <= 232448, "smem");

struct Scratch {
    unsigned epoch;
    unsigned pad0[31];
    float4 acc[2][4][NREP][NVEC + 2];
    unsigned long long qx[2][NCTA][DH];
    unsigned long long ox[2][NCTA][DH + 8];
};
__device__ Scratch g_s;
#define FAIL(code) __trap()

__device__ __forceinline__ float bf16r(float x) { return __bfloat162float(__float2bfloat16_rn(x)); }
__device__ __forceinline__ float bf_lo(unsigned u) { return __uint_as_float(u << 16); }
__device__ __forceinline__ float bf_hi(unsigned u) { return __uint_as_float(u & 0xffff0000u); }
__device__ __forceinline__ uint32_t smem_u32(const void* p) { return (uint32_t)__cvta_generic_to_shared(p); }

__device__ __forceinline__ void bar_comp() { asm volatile("bar.sync 1, 256;" ::: "memory"); }

__device__ __forceinline__ void mbar_init(uint32_t bar, int count) {
    asm volatile("mbarrier.init.shared::cta.b64 [%0], %1;" ::"r"(bar), "r"(count) : "memory");
}
__device__ __forceinline__ void mbar_arrive(uint32_t bar) {
    asm volatile("mbarrier.arrive.shared::cta.b64 _, [%0];" ::"r"(bar) : "memory");
}
__device__ __forceinline__ void mbar_expect_tx(uint32_t bar, int bytes) {
    asm volatile("mbarrier.arrive.expect_tx.shared::cta.b64 _, [%0], %1;" ::"r"(bar), "r"(bytes) : "memory");
}
__device__ __forceinline__ void mbar_wait(uint32_t bar, uint32_t parity, int code = 1) {
    uint32_t done = 0;
#pragma unroll 1
    for (int it = 0; it < SPIN_LIMIT; ++it) {
        asm volatile(
            "{\n.reg .pred p;\n"
            "mbarrier.try_wait.parity.shared::cta.b64 p, [%1], %2;\n"
            "selp.u32 %0, 1, 0, p;\n}\n"
            : "=r"(done) : "r"(bar), "r"(parity) : "memory");
        if (done) return;
    }
    FAIL(code);
}
__device__ __forceinline__ void tma_load_2d(uint32_t dst, const CUtensorMap* tm, int c0, int c1, uint32_t bar,
                                            unsigned long long policy) {
    asm volatile(
        "cp.async.bulk.tensor.2d.shared::cluster.global.mbarrier::complete_tx::bytes.L2::cache_hint "
        "[%0], [%1, {%3, %4}], [%2], %5;"
        ::"r"(dst), "l"((unsigned long long)tm), "r"(bar), "r"(c0), "r"(c1), "l"(policy) : "memory");
}
#define LDSM4(TRANS, a, t0, off)                                                                                   \
    asm volatile(                                                                                                   \
        "ldmatrix.sync.aligned.m8n8.x4" TRANS ".shared.b16 {%0,%1,%2,%3}, [%16];\n"                                 \
        "ldmatrix.sync.aligned.m8n8.x4" TRANS ".shared.b16 {%4,%5,%6,%7}, [%17];\n"                                 \
        "ldmatrix.sync.aligned.m8n8.x4" TRANS ".shared.b16 {%8,%9,%10,%11}, [%18];\n"                               \
        "ldmatrix.sync.aligned.m8n8.x4" TRANS ".shared.b16 {%12,%13,%14,%15}, [%19];\n"                             \
        : "=r"(a[0][0]), "=r"(a[0][1]), "=r"(a[0][2]), "=r"(a[0][3]), "=r"(a[1][0]), "=r"(a[1][1]), "=r"(a[1][2]), \
          "=r"(a[1][3]), "=r"(a[2][0]), "=r"(a[2][1]), "=r"(a[2][2]), "=r"(a[2][3]), "=r"(a[3][0]), "=r"(a[3][1]), \
          "=r"(a[3][2]), "=r"(a[3][3])                                                                              \
        : "r"((t0) + off[0]), "r"((t0) + off[1]), "r"((t0) + off[2]), "r"((t0) + off[3])                            \
        : "memory")
__device__ __forceinline__ void mma_bf16(float* c, const uint32_t* a, uint32_t b0, uint32_t b1) {
    asm volatile(
        "mma.sync.aligned.m16n8k16.row.col.f32.bf16.bf16.f32 {%0,%1,%2,%3}, {%4,%5,%6,%7}, {%8,%9}, {%0,%1,%2,%3};"
        : "+f"(c[0]), "+f"(c[1]), "+f"(c[2]), "+f"(c[3])
        : "r"(a[0]), "r"(a[1]), "r"(a[2]), "r"(a[3]), "r"(b0), "r"(b1));
}
__device__ __forceinline__ void ll_store(unsigned long long* p, float v, unsigned tag) {
    unsigned long long w = ((unsigned long long)tag << 32) | (unsigned long long)__float_as_uint(v);
    asm volatile("st.relaxed.gpu.global.u64 [%0], %1;" ::"l"(p), "l"(w) : "memory");
}
__device__ __forceinline__ unsigned long long ld_rlx64(const unsigned long long* p) {
    unsigned long long w;
    asm volatile("ld.relaxed.gpu.global.u64 %0, [%1];" : "=l"(w) : "l"(p) : "memory");
    return w;
}
__device__ __forceinline__ void ll_wait4(const unsigned long long* p, int stride, unsigned tag, float* v, int code = 2) {
#pragma unroll 1
    for (int it = 0; it < SPIN_LIMIT; ++it) {
        const unsigned long long w0 = ld_rlx64(p), w1 = ld_rlx64(p + stride), w2 = ld_rlx64(p + 2 * stride), w3 = ld_rlx64(p + 3 * stride);
        if ((unsigned)(w0 >> 32) == tag && (unsigned)(w1 >> 32) == tag && (unsigned)(w2 >> 32) == tag && (unsigned)(w3 >> 32) == tag) {
            v[0] = __uint_as_float((unsigned)w0); v[1] = __uint_as_float((unsigned)w1);
            v[2] = __uint_as_float((unsigned)w2); v[3] = __uint_as_float((unsigned)w3);
            return;
        }
    }
    FAIL(code);
}
__device__ __forceinline__ void ll_wait4x2(const unsigned long long* p, const unsigned long long* q, int stride, unsigned tag,
                                           float* v, float* u, int code = 2) {
#pragma unroll 1
    for (int it = 0; it < SPIN_LIMIT; ++it) {
        unsigned long long w[8];
#pragma unroll
        for (int i = 0; i < 4; ++i) { w[i] = ld_rlx64(p + i * stride); w[4 + i] = ld_rlx64(q + i * stride); }
        bool ok = true;
#pragma unroll
        for (int i = 0; i < 8; ++i) ok = ok && ((unsigned)(w[i] >> 32) == tag);
        if (ok) {
#pragma unroll
            for (int i = 0; i < 4; ++i) { v[i] = __uint_as_float((unsigned)w[i]); u[i] = __uint_as_float((unsigned)w[4 + i]); }
            return;
        }
    }
    FAIL(code);
}
__device__ __forceinline__ uint4 ldg_nc(const void* p) {
    uint4 v;
    asm volatile("ld.global.nc.L1::no_allocate.v4.u32 {%0,%1,%2,%3}, [%4];"
                 : "=r"(v.x), "=r"(v.y), "=r"(v.z), "=r"(v.w) : "l"(p));
    return v;
}
__device__ __forceinline__ uint4 ldg_nc_ef(const void* p, unsigned long long pol) {
    uint4 v;
    asm volatile("ld.global.nc.L1::no_allocate.L2::cache_hint.v4.u32 {%0,%1,%2,%3}, [%4], %5;"
                 : "=r"(v.x), "=r"(v.y), "=r"(v.z), "=r"(v.w) : "l"(p), "l"(pol));
    return v;
}
__device__ __forceinline__ float4 ldg_cg4(const float* p) {
    float4 v;
    asm volatile("ld.relaxed.gpu.global.v4.f32 {%0,%1,%2,%3}, [%4];"
                 : "=f"(v.x), "=f"(v.y), "=f"(v.z), "=f"(v.w) : "l"(p) : "memory");
    return v;
}
__device__ __forceinline__ void red_add4(float* p, float4 v) {
    asm volatile("red.relaxed.gpu.global.add.v4.f32 [%0], {%1,%2,%3,%4};"
                 ::"l"(p), "f"(v.x), "f"(v.y), "f"(v.z), "f"(v.w) : "memory");
}
__device__ __forceinline__ void fma8(float* acc, float s, const uint4& w) {
    acc[0] = fmaf(s, bf_lo(w.x), acc[0]); acc[1] = fmaf(s, bf_hi(w.x), acc[1]);
    acc[2] = fmaf(s, bf_lo(w.y), acc[2]); acc[3] = fmaf(s, bf_hi(w.y), acc[3]);
    acc[4] = fmaf(s, bf_lo(w.z), acc[4]); acc[5] = fmaf(s, bf_hi(w.z), acc[5]);
    acc[6] = fmaf(s, bf_lo(w.w), acc[6]); acc[7] = fmaf(s, bf_hi(w.w), acc[7]);
}
__device__ __forceinline__ float warp_sum(float v) {
#pragma unroll
    for (int o = 16; o > 0; o >>= 1) v += __shfl_xor_sync(0xffffffffu, v, o);
    return v;
}
__device__ __forceinline__ float warp_max(float v) {
#pragma unroll
    for (int o = 16; o > 0; o >>= 1) v = fmaxf(v, __shfl_xor_sync(0xffffffffu, v, o));
    return v;
}
__device__ __noinline__ void layernorm_block(const float* src, float* dst, float* red, int tid) {
    const int warp = tid >> 5, lane = tid & 31;
    const bool has2 = tid < 128;
    const float piv = src[0];
    const float v0 = src[tid], v1 = src[tid + 256], v2 = has2 ? src[tid + 512] : piv;
    const float d0 = v0 - piv, d1 = v1 - piv, d2 = v2 - piv;
    float s1 = d0 + d1 + d2, s2 = fmaf(d0, d0, fmaf(d1, d1, d2 * d2));
#pragma unroll
    for (int o = 16; o > 0; o >>= 1) { s1 += __shfl_xor_sync(0xffffffffu, s1, o); s2 += __shfl_xor_sync(0xffffffffu, s2, o); }
    if (lane == 0) { red[warp] = s1; red[8 + warp] = s2; }
    bar_comp();
    const float4 a0 = *reinterpret_cast<const float4*>(red), a1 = *reinterpret_cast<const float4*>(red + 4);
    const float4 b0 = *reinterpret_cast<const float4*>(red + 8), b1 = *reinterpret_cast<const float4*>(red + 12);
    const float m1 = (((a0.x + a0.y) + (a0.z + a0.w)) + ((a1.x + a1.y) + (a1.z + a1.w))) * (1.0f / D_MODEL);
    const float m2 = (((b0.x + b0.y) + (b0.z + b0.w)) + ((b1.x + b1.y) + (b1.z + b1.w))) * (1.0f / D_MODEL);
    const float var = fmaxf(fmaf(-m1, m1, m2), 0.f);
    const float mb = bf16r(piv + m1);
    const float den = bf16r(sqrtf(bf16r(bf16r(var) + 1e-5f)));
    dst[tid] = bf16r(__fdiv_rn(bf16r(v0 - mb), den));
    dst[tid + 256] = bf16r(__fdiv_rn(bf16r(v1 - mb), den));
    if (has2) dst[tid + 512] = bf16r(__fdiv_rn(bf16r(v2 - mb), den));
    bar_comp();
}


__global__ void __launch_bounds__(NTHREADS, 1)
fused_kernel(const __grid_constant__ CUtensorMap tmK, const __grid_constant__ CUtensorMap tmV,
             const __nv_bfloat16* __restrict__ x_in, const __nv_bfloat16* __restrict__ wq,
             const __nv_bfloat16* __restrict__ wo, const __nv_bfloat16* __restrict__ w1,
             const __nv_bfloat16* __restrict__ b1, const __nv_bfloat16* __restrict__ w2,
             const __nv_bfloat16* __restrict__ b2, __nv_bfloat16* __restrict__ out) {
    extern __shared__ __align__(1024) unsigned char smem[];
    const int tid = threadIdx.x;
    const int warp = tid >> 5;
    const int lane = tid & 31;
    const int cta = blockIdx.x;
    const int head = cta >> 2;
    const int quarter = cta & 3;
    const uint32_t sbase = smem_u32(smem);
    const uint32_t bar_full = sbase + SM_BAR;
    const uint32_t bar_empty = sbase + SM_BAR + NSLOT * 8;
    const uint32_t bar_go = sbase + SM_BAR + 2 * NSLOT * 8;

    uint4 wv[11];
    const __nv_bfloat16* wq_p = wq + (size_t)(quarter * 160 + (tid >> 4)) * (NHEAD * DH) + head * DH + (tid & 15) * 8;
    unsigned long long pol_ef;
    asm volatile("createpolicy.fractional.L2::evict_first.b64 %0, 1.0;" : "=l"(pol_ef));
    if (warp < 8) {
#pragma unroll
        for (int i = 0; i < 10; ++i) wv[i] = ldg_nc_ef(wq_p + (size_t)(16 * i) * (NHEAD * DH), pol_ef);
    }
    if (tid == 0) {
        for (int s = 0; s < NSLOT; ++s) { mbar_init(bar_full + s * 8, 1); mbar_init(bar_empty + s * 8, 8); }
        mbar_init(bar_go, 8);
        asm volatile("fence.mbarrier_init.release.cluster;" ::: "memory");
    }
    __syncthreads();

    if (warp >= 8) {
        asm volatile("setmaxnreg.dec.sync.aligned.u32 24;");
        if (warp == 8 && lane == 0) {
            unsigned long long pol_first, pol_norm;
            asm volatile("createpolicy.fractional.L2::evict_first.b64 %0, 1.0;" : "=l"(pol_first));
            asm volatile("createpolicy.fractional.L2::evict_normal.b64 %0, 1.0;" : "=l"(pol_norm));
            const int row0 = head * SK + quarter * 1024;
            uint32_t used = 0, epar = 0, ppar = 0;
            int hist[INFLIGHT];
#pragma unroll
            for (int i = 0; i < INFLIGHT; ++i) hist[i] = -1;
#pragma unroll 1
            for (int n = 0; n < 64; ++n) {
                const int pass = n >> 5, t = n & 31;
                if (pass == 1 && (t < RETAIN || (t >= NSLOT && t < 16) || t >= 32 - VREG)) continue;
                if (n == NPRE) {
                    mbar_wait(bar_go, 0, 9);
                    asm volatile("cp.async.bulk.prefetch.L2.global.L2::cache_hint [%0], %1, %2;"
                                 ::"l"(wo + (size_t)(head * DH + quarter * 32) * D_MODEL), "r"(32 * D_MODEL * 2), "l"(pol_first) : "memory");
                }
                if (n == 32 + NSLOT + 3) {
                    asm volatile("cp.async.bulk.prefetch.L2.global.L2::cache_hint [%0], %1, %2;"
                                 ::"l"(wo + (size_t)(head * DH + quarter * 32) * D_MODEL), "r"(32 * D_MODEL * 2), "l"(pol_first) : "memory");
                }
                const unsigned long long tabv = (t < 16) ? (pass ? SLOTS_K1 : SLOTS_K0) : (pass ? SLOTS_V1 : SLOTS_V0);
                const int s = (int)(tabv >> (4 * (t & 15))) & 15;
                if (used & (1u << s)) { mbar_wait(bar_empty + s * 8, (epar >> s) & 1, 10 + n); epar ^= (1u << s); }
                used |= (1u << s);
                {
                    bool skip = hist[0] < 0 || (hist[0] & 15) == s;
#pragma unroll
                    for (int i = 1; i < INFLIGHT; ++i) skip = skip || ((hist[i] & 15) == (hist[0] & 15));
                    if (!skip && pass == 0) mbar_wait(bar_full + (hist[0] & 15) * 8, hist[0] >> 4, 8);
                }
#pragma unroll
                for (int i = 0; i + 1 < INFLIGHT; ++i) hist[i] = hist[i + 1];
                hist[INFLIGHT - 1] = s | (((ppar >> s) & 1) << 4);
                ppar ^= (1u << s);
                const CUtensorMap* tm = (t < 16) ? &tmK : &tmV;
                const int row = row0 + (t & 15) * TILE_KEYS;
                const unsigned long long pol = (pass == 1 || t < 16 || t >= 32 - VREG) ? pol_first : pol_norm;
                const uint32_t dst = sbase + SM_SLOTS + s * TILE_BYTES;
                mbar_expect_tx(bar_full + s * 8, TILE_BYTES);
                tma_load_2d(dst, tm, 0, row, bar_full + s * 8, pol);
                tma_load_2d(dst + TILE_BYTES / 2, tm, 64, row, bar_full + s * 8, pol);
            }
        }
        return;
    }

    asm volatile("setmaxnreg.inc.sync.aligned.u32 240;");
    float* scores = reinterpret_cast<float*>(smem + SM_A);
    __nv_bfloat16* pbf = reinterpret_cast<__nv_bfloat16*>(smem + SM_P);
    float* gscr = reinterpret_cast<float*>(smem + SM_A);
    float* redb = reinterpret_cast<float*>(smem + SM_B);
    float* xn_s = reinterpret_cast<float*>(smem + SM_XN);
    float* xs = reinterpret_cast<float*>(smem + SM_XS);
    float* misc = reinterpret_cast<float*>(smem + SM_MISC);
    const int g = lane >> 2, t4 = lane & 3;
    const int half = warp >> 2, grp = warp & 3;
    const int chunk = tid % 80, rg = tid / 80;

    unsigned epoch;
    asm volatile("ld.relaxed.gpu.global.u32 %0, [%1];" : "=r"(epoch) : "l"(&g_s.epoch) : "memory");
    const int par = epoch & 1;
    if (tid < 160) {
        const uint2 u = *reinterpret_cast<const uint2*>(x_in + tid * 4);
        *reinterpret_cast<float4*>(xs + tid * 4) = make_float4(bf_lo(u.x), bf_hi(u.x), bf_lo(u.y), bf_hi(u.y));
    }
    bar_comp();

    uint32_t fpar = 0;
    uint32_t vr[VREG][4][4];
    uint32_t kr[KREG][4][4];

#pragma unroll 1
    for (int layer = 0; layer < 2; ++layer) {
        const unsigned tag = epoch * 2 + layer + 1;
        layernorm_block(xs, xn_s, misc, tid);
        {
            float acc[8];
#pragma unroll
            for (int i = 0; i < 8; ++i) acc[i] = 0.f;
#pragma unroll
            for (int i = 0; i < 10; ++i) fma8(acc, xn_s[quarter * 160 + (tid >> 4) + 16 * i], wv[i]);
            if (layer == 0) { __syncwarp(); if (lane == 0) mbar_arrive(bar_go); }
#pragma unroll
            for (int i = 0; i < 8; ++i) acc[i] += __shfl_xor_sync(0xffffffffu, acc[i], 16);
            if (lane < 16) {
                *reinterpret_cast<float4*>(redb + warp * 128 + lane * 8) = make_float4(acc[0], acc[1], acc[2], acc[3]);
                *reinterpret_cast<float4*>(redb + warp * 128 + lane * 8 + 4) = make_float4(acc[4], acc[5], acc[6], acc[7]);
            }
        }
        bar_comp();
        if (tid < 128) {
            float s = 0.f;
#pragma unroll
            for (int w = 0; w < 8; ++w) s += redb[w * 128 + tid];
            ll_store(&g_s.qx[layer][cta][tid], s, tag);
            float qp[4];
            ll_wait4(&g_s.qx[layer][head * 4][tid], DH, tag, qp, 20);
            reinterpret_cast<__nv_bfloat16*>(misc + 64)[tid] = __float2bfloat16_rn((qp[0] + qp[1]) + (qp[2] + qp[3]));
        } else if (layer == 0) {
            const int i = tid - 128;
            constexpr int ZPC = 4 * NREP * (NVEC + 2) / NCTA;
            if (i < ZPC) (&g_s.acc[par ^ 1][0][0][0])[cta * ZPC + i] = make_float4(0.f, 0.f, 0.f, 0.f);
        }
        bar_comp();
        uint32_t qb[8];
        {
            const uint32_t* qw = reinterpret_cast<const uint32_t*>(misc + 64) + half * 32;
#pragma unroll
            for (int kk = 0; kk < 4; ++kk) {
                qb[kk * 2] = (g == 0) ? qw[kk * 8 + t4] : 0u;
                qb[kk * 2 + 1] = (g == 0) ? qw[kk * 8 + 4 + t4] : 0u;
            }
        }
        {
            const int row = grp * 16 + (lane & 7) + ((lane >> 3) & 1) * 8;
            uint32_t off[4];
#pragma unroll
            for (int kk = 0; kk < 4; ++kk) off[kk] = sbase + SM_SLOTS + half * 8192 + row * 128 + (((kk * 2 + (lane >> 4)) ^ (row & 7)) << 4);
            const unsigned long long tab = layer ? SLOTS_K1 : SLOTS_K0;
            const int nres = layer ? RETAIN : 0;
            const int nkeep = layer ? 0 : RETAIN;
            float* sp = scores + half * 1024 + grp * 16 + g;
            uint32_t fa[4][4], fb[4][4];
#define K_LOAD(F, C) do { const int s_ = (int)(tab >> (4 * (C))) & 15; \
                if ((C) >= nres) { mbar_wait(bar_full + s_ * 8, (fpar >> s_) & 1, 80 + layer * 32 + (C)); fpar ^= (1u << s_); } \
                LDSM4("", F, s_ * TILE_BYTES, off); } while (0)
#define K_MMA(F, C) do { float c0[4] = {0.f, 0.f, 0.f, 0.f}, c1[4] = {0.f, 0.f, 0.f, 0.f}; \
                mma_bf16(c0, F[0], qb[0], qb[1]); mma_bf16(c1, F[1], qb[2], qb[3]); \
                mma_bf16(c0, F[2], qb[4], qb[5]); mma_bf16(c1, F[3], qb[6], qb[7]); \
                __syncwarp(); \
                if (lane == 0 && (C) >= nkeep) mbar_arrive(bar_empty + ((int)(tab >> (4 * (C))) & 15) * 8); \
                if (t4 == 0) { sp[(C) * 64] = c0[0] + c1[0]; sp[(C) * 64 + 8] = c0[2] + c1[2]; } } while (0)
#define K_MMA_NOREL(F, C) do { float c0[4] = {0.f, 0.f, 0.f, 0.f}, c1[4] = {0.f, 0.f, 0.f, 0.f}; \
                mma_bf16(c0, F[0], qb[0], qb[1]); mma_bf16(c1, F[1], qb[2], qb[3]); \
                mma_bf16(c0, F[2], qb[4], qb[5]); mma_bf16(c1, F[3], qb[6], qb[7]); \
                if (t4 == 0) { sp[(C) * 64] = c0[0] + c1[0]; sp[(C) * 64 + 8] = c0[2] + c1[2]; } } while (0)
            K_LOAD(fa, 0);
#pragma unroll 1
            for (int c = 0; c < NSLOT - 1; c += 2) {
                K_LOAD(fb, c + 1);
                K_MMA(fa, c);
                K_LOAD(fa, c + 2);
                K_MMA(fb, c + 1);
            }
            K_MMA(fa, NSLOT - 1);
            if (layer == 0) {
#pragma unroll
                for (int c = 0; c < KREG; ++c) K_LOAD(kr[c], NSLOT + c);
            }
#pragma unroll
            for (int c = 0; c < KREG; ++c) { if (layer == 0) K_MMA(kr[c], NSLOT + c); else K_MMA_NOREL(kr[c], NSLOT + c); }
        }
        bar_comp();
        {
            const __nv_bfloat16* wp = wo + (size_t)(head * DH + quarter * 32 + rg) * D_MODEL + chunk * 8;
#pragma unroll
            for (int i = 0; i < 11; ++i)
                if (tid < 240 && rg + 3 * i < 32) wv[i] = ldg_nc_ef(wp + (size_t)(3 * i) * D_MODEL, pol_ef);
        }
        float sc[4];
        {
            const float4 s0 = *reinterpret_cast<const float4*>(scores + tid * 4);
            const float4 s1 = *reinterpret_cast<const float4*>(scores + 1024 + tid * 4);
            sc[0] = bf16r(bf16r(s0.x + s1.x) * 0.08838834764831845f);
            sc[1] = bf16r(bf16r(s0.y + s1.y) * 0.08838834764831845f);
            sc[2] = bf16r(bf16r(s0.z + s1.z) * 0.08838834764831845f);
            sc[3] = bf16r(bf16r(s0.w + s1.w) * 0.08838834764831845f);
            const float wmax = warp_max(fmaxf(fmaxf(sc[0], sc[1]), fmaxf(sc[2], sc[3])));
            if (lane == 0) misc[warp] = wmax;
        }
        bar_comp();
        float mloc;
        {
            const float4 r0 = *reinterpret_cast<const float4*>(misc), r1 = *reinterpret_cast<const float4*>(misc + 4);
            mloc = fmaxf(fmaxf(fmaxf(r0.x, r0.y), fmaxf(r0.z, r0.w)), fmaxf(fmaxf(r1.x, r1.y), fmaxf(r1.z, r1.w)));
            const float e0 = __expf(sc[0] - mloc), e1 = __expf(sc[1] - mloc), e2 = __expf(sc[2] - mloc), e3 = __expf(sc[3] - mloc);
            __nv_bfloat162 p01 = __floats2bfloat162_rn(e0, e1), p23 = __floats2bfloat162_rn(e2, e3);
            uint2 pk;
            pk.x = *reinterpret_cast<uint32_t*>(&p01); pk.y = *reinterpret_cast<uint32_t*>(&p23);
            *reinterpret_cast<uint2*>(pbf + tid * 4) = pk;
            float ls = warp_sum((e0 + e1) + (e2 + e3));
            if (lane == 0) misc[8 + warp] = ls;
        }
        bar_comp();
        float oa[4][4];
#pragma unroll
        for (int dd = 0; dd < 4; ++dd) { oa[dd][0] = oa[dd][1] = oa[dd][2] = oa[dd][3] = 0.f; }
        {
            const int key = grp * 16 + (lane & 7) + (lane >> 4) * 8;
            uint32_t off[4];
#pragma unroll
            for (int dd = 0; dd < 4; ++dd) off[dd] = sbase + SM_SLOTS + half * 8192 + key * 128 + (((dd * 2 + ((lane >> 3) & 1)) ^ (key & 7)) << 4);
            const uint32_t* pw0 = reinterpret_cast<const uint32_t*>(pbf + grp * 16) + t4;
            const unsigned long long tab = layer ? SLOTS_V1 : SLOTS_V0;
#define V_LOAD(F, C) do { const int s_ = (int)(tab >> (4 * (C))) & 15; \
                mbar_wait(bar_full + s_ * 8, (fpar >> s_) & 1, 96 + layer * 32 + (C)); fpar ^= (1u << s_); \
                LDSM4(".trans", F, s_ * TILE_BYTES, off); } while (0)
#define V_MMA(F, C) do { const uint32_t b0_ = (g == 0) ? pw0[(C) * 32] : 0u, b1_ = (g == 0) ? pw0[(C) * 32 + 4] : 0u; \
                mma_bf16(oa[0], F[0], b0_, b1_); mma_bf16(oa[1], F[1], b0_, b1_); \
                mma_bf16(oa[2], F[2], b0_, b1_); mma_bf16(oa[3], F[3], b0_, b1_); } while (0)
#define V_REL(C) do { __syncwarp(); if (lane == 0) mbar_arrive(bar_empty + ((int)(tab >> (4 * (C))) & 15) * 8); } while (0)
            if (layer == 1) {
#pragma unroll
                for (int c = 0; c < VREG; ++c) V_MMA(vr[c], 16 - VREG + c);
            }
            uint32_t fa[4][4], fb[4][4];
            constexpr int NV = 16 - VREG;
            V_LOAD(fa, 0);
#pragma unroll 1
            for (int c = 0; c + 1 < NV; c += 2) {
                V_LOAD(fb, c + 1);
                V_MMA(fa, c); V_REL(c);
                if (c + 2 < NV) V_LOAD(fa, c + 2);
                V_MMA(fb, c + 1); V_REL(c + 1);
            }
            if (NV & 1) { V_MMA(fa, NV - 1); V_REL(NV - 1); }
            if (layer == 0) {
#pragma unroll
                for (int c = 0; c < VREG; ++c) {
                    V_LOAD(vr[c], 16 - VREG + c);
                    V_MMA(vr[c], 16 - VREG + c); V_REL(16 - VREG + c);
                }
            }
        }
        if (layer == 0 && cta < MLP_CTAS) {
            for (int r = tid; r < D_MODEL; r += NCOMP)
                asm volatile("prefetch.global.L2 [%0];" ::"l"(w1 + (size_t)r * FF + cta * 16));
            if (tid < 160) asm volatile("prefetch.global.L2 [%0];" ::"l"(w2 + (size_t)(cta * 16) * D_MODEL + tid * 64));
        }
        if (t4 == 0) {
#pragma unroll
            for (int dd = 0; dd < 4; ++dd) {
                redb[grp * 128 + half * 64 + dd * 16 + g] = oa[dd][0];
                redb[grp * 128 + half * 64 + dd * 16 + g + 8] = oa[dd][2];
            }
        }
        bar_comp();
        if (tid < 128) {
            float s = (redb[tid] + redb[128 + tid]) + (redb[256 + tid] + redb[384 + tid]);
            ll_store(&g_s.ox[layer][cta][tid], s, tag);
        } else if (tid < 130) {
            const float4 r0 = *reinterpret_cast<const float4*>(misc + 8), r1 = *reinterpret_cast<const float4*>(misc + 12);
            const float lloc = ((r0.x + r0.y) + (r0.z + r0.w)) + ((r1.x + r1.y) + (r1.z + r1.w));
            ll_store(&g_s.ox[layer][cta][tid], tid == 128 ? mloc : lloc, tag);
        }
        if (warp == 7) {
            float op[4], ms[4];
            ll_wait4x2(&g_s.ox[layer][head * 4][quarter * 32 + lane], &g_s.ox[layer][head * 4][128 + (lane & 1)], DH + 8, tag, op, ms, 21);
            float mm[4], ll[4];
#pragma unroll
            for (int pp = 0; pp < 4; ++pp) { mm[pp] = __shfl_sync(0xffffffffu, ms[pp], 0); ll[pp] = __shfl_sync(0xffffffffu, ms[pp], 1); }
            const float M = fmaxf(fmaxf(mm[0], mm[1]), fmaxf(mm[2], mm[3]));
            float L = 0.f, o = 0.f;
#pragma unroll
            for (int pp = 0; pp < 4; ++pp) { const float wgt = __expf(mm[pp] - M); L = fmaf(ll[pp], wgt, L); o = fmaf(op[pp], wgt, o); }
            misc[32 + lane] = bf16r(__fdiv_rn(o, L));
        }
        bar_comp();
        int nrows = 32;
#pragma unroll 1
        for (int sub = 0; sub < 2; ++sub) {
            const int ph = layer * 2 + sub;
            if (tid < 240) {
                float acc[8];
#pragma unroll
                for (int i = 0; i < 8; ++i) acc[i] = 0.f;
#pragma unroll
                for (int i = 0; i < 11; ++i)
                    if (rg + 3 * i < nrows) fma8(acc, misc[32 + rg + 3 * i], wv[i]);
                *reinterpret_cast<float4*>(gscr + rg * 640 + chunk * 8) = make_float4(acc[0], acc[1], acc[2], acc[3]);
                *reinterpret_cast<float4*>(gscr + rg * 640 + chunk * 8 + 4) = make_float4(acc[4], acc[5], acc[6], acc[7]);
            }
            bar_comp();
            if (tid < NVEC && nrows > 0) {
                float v[3];
#pragma unroll
                for (int k = 0; k < 3; ++k) {
                    const int idx = tid * 3 + k;
                    v[k] = idx < D_MODEL ? (gscr[idx] + gscr[640 + idx]) + gscr[1280 + idx] : 0.f;
                }
                red_add4(reinterpret_cast<float*>(&g_s.acc[par][ph][cta % NREP][tid]), make_float4(v[0], v[1], v[2], 1.0f));
            }
            if (ph == 3 && cta != 0) return;
            if (ph == 0 && tid < 160) {
                const __nv_bfloat16* pp = wq + (size_t)(quarter * 160 + tid) * (NHEAD * DH) + head * DH;
                asm volatile("prefetch.global.L2 [%0];" ::"l"(pp));
                asm volatile("prefetch.global.L2 [%0];" ::"l"(pp + 64));
            }
            uint4 w1v[5];
            float bv = 0.f;
            if (sub == 0) {
                if (cta < MLP_CTAS) {
                    const __nv_bfloat16* wp = w1 + (size_t)(tid >> 1) * FF + cta * 16 + (tid & 1) * 8;
#pragma unroll
                    for (int i = 0; i < 5; ++i) w1v[i] = ldg_nc(wp + (size_t)(128 * i) * FF);
                    const __nv_bfloat16* wp2 = w2 + (size_t)(cta * 16 + rg) * D_MODEL + chunk * 8;
#pragma unroll
                    for (int i = 0; i < 6; ++i)
                        if (tid < 240 && rg + 3 * i < 16) wv[i] = ldg_nc(wp2 + (size_t)(3 * i) * D_MODEL);
                    if (tid < 16) bv = __bfloat162float(b1[cta * 16 + tid]);
                }
            } else if (layer == 0) {
#pragma unroll
                for (int i = 0; i < 10; ++i) wv[i] = ldg_nc_ef(wq_p + (size_t)(16 * i) * (NHEAD * DH), pol_ef);
            }
            if (tid < NVEC) {
                float bb[3] = {0.f, 0.f, 0.f};
                if (sub == 1) {
#pragma unroll
                    for (int k = 0; k < 3; ++k) if (tid * 3 + k < D_MODEL) bb[k] = __bfloat162float(b2[tid * 3 + k]);
                }
                const int ncontrib = sub ? MLP_CTAS : NCTA;
                float4 v[NREP];

#pragma unroll 1
                for (int it = 0;; ++it) {
                    bool ok = true;
#pragma unroll
                    for (int r = 0; r < NREP; ++r) v[r] = ldg_cg4(reinterpret_cast<const float*>(&g_s.acc[par][ph][r][tid]));
#pragma unroll
                    for (int r = 0; r < NREP; ++r) ok = ok && (v[r].w == (float)((ncontrib - r + NREP - 1) / NREP));
                    if (ok) break;
                    if (it >= SPIN_LIMIT) { FAIL(3 + ph); break; }
                }
                float sx = v[0].x, sy = v[0].y, sz = v[0].z;
#pragma unroll
                for (int r = 1; r < NREP; ++r) { sx += v[r].x; sy += v[r].y; sz += v[r].z; }
                float sv[3] = {bf16r(sx), bf16r(sy), bf16r(sz)};
#pragma unroll
                for (int k = 0; k < 3; ++k) {
                    const int idx = tid * 3 + k;
                    if (idx < D_MODEL) {
                        const float d = sub ? bf16r(sv[k] + bb[k]) : sv[k];
                        xs[idx] = bf16r(xs[idx] + d);
                    }
                }
            }
            bar_comp();
            if (sub == 0) {
                nrows = 0;
                if (cta < MLP_CTAS) {
                    nrows = 16;
                    layernorm_block(xs, xn_s, misc, tid);
                    layernorm_block(xn_s, xn_s, misc, tid);
                    float acc[8];
#pragma unroll
                    for (int i = 0; i < 8; ++i) acc[i] = 0.f;
#pragma unroll
                    for (int i = 0; i < 5; ++i) fma8(acc, xn_s[(tid >> 1) + 128 * i], w1v[i]);
#pragma unroll
                    for (int o = 2; o <= 16; o <<= 1)
#pragma unroll
                        for (int i = 0; i < 8; ++i) acc[i] += __shfl_xor_sync(0xffffffffu, acc[i], o);
                    if (lane < 2) {
                        *reinterpret_cast<float4*>(redb + warp * 16 + lane * 8) = make_float4(acc[0], acc[1], acc[2], acc[3]);
                        *reinterpret_cast<float4*>(redb + warp * 16 + lane * 8 + 4) = make_float4(acc[4], acc[5], acc[6], acc[7]);
                    }
                    bar_comp();
                    if (tid < 16) {
                        float s = 0.f;
#pragma unroll
                        for (int w = 0; w < 8; ++w) s += redb[w * 16 + tid];
                        const float u = bf16r(bf16r(s) + bv);
                        const float inner = 0.7978845608028654f * (u + 0.044715f * u * u * u);
                        misc[32 + tid] = bf16r(0.5f * u * (1.0f + tanhf(inner)));
                    }
                    bar_comp();
                }
            }
        }
    }
    if (tid < 160) {
        const float4 x = *reinterpret_cast<const float4*>(xs + tid * 4);
        __nv_bfloat162 a = __floats2bfloat162_rn(x.x, x.y);
        __nv_bfloat162 b = __floats2bfloat162_rn(x.z, x.w);
        uint2 u;
        u.x = *reinterpret_cast<uint32_t*>(&a); u.y = *reinterpret_cast<uint32_t*>(&b);
        *reinterpret_cast<uint2*>(out + tid * 4) = u;
        if (tid == 0) asm volatile("st.relaxed.gpu.global.u32 [%0], %1;" ::"l"(&g_s.epoch), "r"(epoch + 1) : "memory");
    }
}

typedef CUresult (*EncodeFn)(CUtensorMap*, CUtensorMapDataType, cuuint32_t, void*, const cuuint64_t*, const cuuint64_t*,
                             const cuuint32_t*, const cuuint32_t*, CUtensorMapInterleave, CUtensorMapSwizzle,
                             CUtensorMapL2promotion, CUtensorMapFloatOOBfill);

void make_map(EncodeFn fn, CUtensorMap* tm, const void* ptr) {
    cuuint64_t gdim[2] = {(cuuint64_t)DH, (cuuint64_t)NHEAD * SK};
    cuuint64_t gstr[1] = {(cuuint64_t)DH * 2};
    cuuint32_t box[2] = {64, (cuuint32_t)TILE_KEYS};
    cuuint32_t estr[2] = {1, 1};
    fn(tm, CU_TENSOR_MAP_DATA_TYPE_BFLOAT16, 2, const_cast<void*>(ptr), gdim, gstr, box, estr,
       CU_TENSOR_MAP_INTERLEAVE_NONE, CU_TENSOR_MAP_SWIZZLE_128B, CU_TENSOR_MAP_L2_PROMOTION_L2_128B,
       CU_TENSOR_MAP_FLOAT_OOB_FILL_NONE);
}

}

extern "C" void kernel_launch(void* const* d_in, const int* in_sizes, int n_in, void* d_out, int out_size) {
    static EncodeFn encode = nullptr;
    if (!encode) {
        void* fn = nullptr;
        cudaDriverEntryPointQueryResult st;
        cudaGetDriverEntryPoint("cuTensorMapEncodeTiled", &fn, cudaEnableDefault, &st);
        encode = (EncodeFn)fn;
        cudaFuncSetAttribute(fused_kernel, cudaFuncAttributeMaxDynamicSharedMemorySize, SM_TOTAL);
    }
    CUtensorMap tmK, tmV;
    make_map(encode, &tmK, d_in[1]);
    make_map(encode, &tmV, d_in[2]);
    fused_kernel<<<NCTA, NTHREADS, SM_TOTAL>>>(
        tmK, tmV, (const __nv_bfloat16*)d_in[0], (const __nv_bfloat16*)d_in[3], (const __nv_bfloat16*)d_in[4],
        (const __nv_bfloat16*)d_in[6], (const __nv_bfloat16*)d_in[7], (const __nv_bfloat16*)d_in[8],
        (const __nv_bfloat16*)d_in[9], (__nv_bfloat16*)d_out);
}
```
